```python
import torch

def _softmax(x, axis=-1):
    return torch.softmax(x, dim=axis)
def _gelu(x):
    return torch.nn.functional.gelu(x, approximate="tanh")
def _silu(x):
    return torch.nn.functional.silu(x)
def _sigmoid(x):
    return torch.sigmoid(x)
def _layernorm(x, axis=-1, eps=1e-5):
    m = x.mean(dim=axis, keepdim=True)
    v = x.var(dim=axis, keepdim=True, unbiased=False)
    return (x - m) / torch.sqrt(v + eps)
def _scatter_add(tgt, idx, src, axis=0):
    return tgt.clone().index_add_(axis, idx, src)
def _segment_sum(src, seg, n):
    out = torch.zeros((n,) + src.shape[1:], dtype=src.dtype)
    return out.index_add_(0, seg, src)
def _pad(x, pw):
    flat = tuple(v for pair in reversed(pw) for v in pair)
    return torch.nn.functional.pad(x, flat)

kernel_name = 'standalone__structured_sparse_n_m__ragged'

def setup_inputs():

    _w = (lambda a: (lambda t: t.to(torch.bfloat16) if t.is_floating_point() else t)(torch.as_tensor(a)))
    B, S, D = 16, 4096, 576
    assert D % 4 == 0, "d_model must be divisible by M=4 for 2:4 sparsity"
    return {
        "x": _w((lambda *s: torch.randn(*s, dtype=torch.bfloat16) * 0.05)(B, S, D)),
        "w": _w((lambda *s: torch.randn(*s, dtype=torch.bfloat16) * 0.05)(D, D)),
        "b": _w((lambda *s: torch.randn(*s, dtype=torch.bfloat16) * 0.05)(D)),
    }

def reference(x, w, b):
    B, S, D = x.shape
    N, M = 2, 4
    G = D // M
    wg = w.reshape(G, M, D)
    mag = torch.abs(wg)
    order = torch.argsort(mag, 1)
    thr = (lambda x, i, axis: torch.take_along_dim(x, i, dim=axis))(mag, order[:, M - N:M - N + 1, :], 1)
    mask = (lambda x, dt: x.to(dt))(mag >= thr, w.dtype)
    wp = (wg * mask).reshape(D, D)
    return torch.einsum("bsd,df->bsf", x, wp) + b
```

```cpp
#include <cuda_runtime.h>
#include <cuda_bf16.h>
#include <cuda.h>
#include <stdint.h>

constexpr int D = 576;
constexpr int NT = 48;
constexpr int NSLOT = 3;
constexpr int SPLIT = 13;
constexpr int KSTEPS = 18;
constexpr int CL = 3;
constexpr int TILE_BYTES = NT * D * 2;
constexpr int STG_BYTES = NT * 128;
constexpr int NACC = NT / 2;
constexpr int NB = NT / 8;
constexpr int NCONS = 384;
constexpr int NTHREADS = 512;
constexpr uint32_t NO_TILE = 0xFFFFFFFFu;

constexpr int OFF_X = 0;
constexpr int OFF_STG = OFF_X + NSLOT * TILE_BYTES;
constexpr int OFF_WST = OFF_STG;
constexpr int OFF_FULL = OFF_STG + (3 * STG_BYTES > 192 * 128 ? 3 * STG_BYTES : 192 * 128);
constexpr int OFF_EMPTY = OFF_FULL + 8 * NSLOT;
constexpr int OFF_MBAR = OFF_EMPTY + 8 * NSLOT;
constexpr int OFF_GO = OFF_MBAR + 16;
constexpr int OFF_EPOCH = OFF_GO + 8;
constexpr int OFF_TK = OFF_EPOCH + 16;
constexpr int OFF_MSK = OFF_TK + 32;
constexpr int SMEM_BYTES = OFF_MSK + 2 * 36 * 4 + 1024;
static_assert(SMEM_BYTES <= 232448 && NSLOT < 8, "layout");
constexpr int BAR_T = 4, BAR_SFULL = 7, BAR_SEMPTY = 10, BAR_G = 13;

constexpr int SCR_M = 9 * KSTEPS * 2048, SCR_S = SCR_M + 36 * KSTEPS * 64, SCR_I = SCR_S + 36 * 2048, SCR_END = SCR_I + 36 * 128;
__device__ __align__(128) uint4    g_scr[2][SCR_END / 16];
__device__ __align__(128) uint4    g_over[36 * 144 * 8];
__device__ __align__(128) uint32_t g_epoch;
__device__ __align__(128) uint32_t g_passed;
__device__ __align__(128) uint32_t g_ticket;

__device__ __forceinline__ uint32_t now() { uint32_t c; asm volatile("mov.u32 %0, %%globaltimer_lo;" : "=r"(c)); return c; }
__device__ __forceinline__ void wait_until(uint32_t due) { while ((int)(now() - due) < 0) __nanosleep(20); }

__device__ __forceinline__ uint32_t max2(uint32_t a, uint32_t b) { uint32_t d; asm("max.u16x2 %0, %1, %2;" : "=r"(d) : "r"(a), "r"(b)); return d; }
__device__ __forceinline__ uint32_t min2(uint32_t a, uint32_t b) { uint32_t d; asm("min.u16x2 %0, %1, %2;" : "=r"(d) : "r"(a), "r"(b)); return d; }
__device__ __forceinline__ uint32_t sign2(uint32_t a) { uint32_t d; asm("prmt.b32 %0, %1, %1, 0xBB99;" : "=r"(d) : "r"(a)); return d; }
__device__ __forceinline__ void zip4(uint32_t a01, uint32_t a23, uint32_t b01, uint32_t b23, uint32_t (&x)[4]) {
    x[0] = __byte_perm(a01, b01, 0x5410); x[1] = __byte_perm(a01, b01, 0x7632); x[2] = __byte_perm(a23, b23, 0x5410); x[3] = __byte_perm(a23, b23, 0x7632);
}
__device__ __forceinline__ void middle2(const uint32_t (&x)[4], uint32_t (&m)[4], uint32_t& u, uint32_t& v) {
#pragma unroll
    for (int i = 0; i < 4; i++) m[i] = x[i] & 0x7FFF7FFFu;
    u = min2(max2(m[0], m[1]), max2(m[2], m[3])); v = max2(min2(m[0], m[1]), min2(m[2], m[3]));
}
__device__ __forceinline__ bool has_tie(uint32_t x0, uint32_t x1, uint32_t x2, uint32_t x3) {
    const uint32_t x[4] = {x0, x1, x2, x3};
    uint32_t m[4], u, v;
    middle2(x, m, u, v);
    const uint32_t t = u ^ v;
    return ((t & 0xFFFFu) == 0 && (v & 0xFFFFu) != 0) || (t < 0x10000u && v >= 0x10000u);
}
__device__ __forceinline__ void load_unit(uint32_t wsm, int ls, int unit, int lane, uint32_t (&m)[4]) {
    const int row = ls * 32 + (lane >> 4) * 16 + ((lane & 7) >> 1) * 4 + ((lane >> 3) & 1) * 2 + (lane & 1);
    const uint32_t ad = wsm + row * 128 + ((unit ^ ((row & 1) | ((row >> 1) & 6))) << 4);
    asm volatile("ldmatrix.sync.aligned.m8n8.x4.trans.shared.b16 {%0,%1,%2,%3}, [%4];" : "=r"(m[0]), "=r"(m[1]), "=r"(m[2]), "=r"(m[3]) : "r"(ad) : "memory");
}
__device__ __forceinline__ void split_pair(const uint32_t (&x)[4], bool P, uint32_t& alo, uint32_t& ahi, uint32_t& nib, uint32_t& rlo, uint32_t& rhi) {
    uint32_t m[4], u, v;
    middle2(x, m, u, v);
    const uint32_t c = 0x80008000u - max2(max2(u, v), 0x00010001u);
    uint32_t k0 = sign2(m[0] + c), k1 = sign2(m[1] + c), k2 = sign2(m[2] + c), k3 = sign2(m[3] + c);
    const uint32_t three = (k0 & k1 & (k2 | k3)) | (k2 & k3 & (k0 | k1)), four = k0 & k1 & k2 & k3;
    const uint32_t pa = P ? k2 : k0, pb = P ? k3 : k1;
    const uint32_t ra = three & pa, rb = three & pb & (four | ~pa);
    const uint32_t va = (P ? x[2] : x[0]) & ra, vb = (P ? x[3] : x[1]) & rb;
    if (P) { k2 &= ~ra; k3 &= ~rb; } else { k0 &= ~ra; k1 &= ~rb; }
    const uint32_t s1 = k1 & k0, s2 = k2 & (k0 | k1);
    const uint32_t t = (k1 & x[1]) | (~k1 & k2 & x[2]);
    const uint32_t x0 = (k0 & x[0]) | (~k0 & t), x1 = (s1 & x[1]) | (s2 & x[2]) | (k3 & x[3]);
    nib = (~k0 & k1 & 0x00010001u) | (~k0 & ~k1 & 0x00020002u) | (~s2 & 0x00040004u) | (~s1 & 0x00080008u);
    alo = __byte_perm(x0, x1, 0x5410); ahi = __byte_perm(x0, x1, 0x7632);
    rlo = __byte_perm(va, vb, 0x5410); rhi = __byte_perm(va, vb, 0x7632);
}
__device__ __forceinline__ uint32_t nonzero(uint32_t v) { return v ? v : 0x8000u; }
__device__ __forceinline__ void pub32(void* a, uint32_t v) { asm volatile("st.relaxed.gpu.global.u32 [%0], %1;" :: "l"(a), "r"(v) : "memory"); }
__device__ __forceinline__ void pub128(bool c, void* a, uint32_t x, uint32_t y, uint32_t z, uint32_t w) {
    asm volatile("{\n.reg .pred p;\n.reg .b64 s, t;\n.reg .b128 v;\nsetp.ne.u32 p, %5, 0;\nmov.b64 s, {%1, %2};\nmov.b64 t, {%3, %4};\nmov.b128 v, {s, t};\n@p st.relaxed.gpu.global.b128 [%0], v;\n}\n"
                 :: "l"(a), "r"(x), "r"(y), "r"(z), "r"(w), "r"((uint32_t)c) : "memory");
}
constexpr int RO_BIAS = 16;
__device__ __forceinline__ uint32_t resid_off(int g, int P, int r) {
    int k0 = 4 * g + 2 * P;
    int chunk = k0 >> 6, byte = (k0 & 63) * 2;
    return chunk * 1024 + r * 128 + (((byte >> 4) ^ r) << 4) + (byte & 15);
}
__device__ __forceinline__ void emit_step(const uint32_t (&lo)[4], const uint32_t (&hi)[4], uint32_t mm, int rb, int ks, int lane, uint32_t units, uint2 bias2,
                                          uint8_t* scr, uint4* over, uint32_t tag) {
    uint8_t* const s0 = scr + SCR_S + rb * 2048 + (lane >> 2) * 16;
    uint8_t* const s1 = (uint8_t*)(over + rb * 144 * 8 + (lane >> 2));
    auto put_slot = [&](bool c, int sl, uint32_t v0, uint32_t v1, uint32_t off) {
        pub128(c, (sl < 16 ? s0 : s1) + sl * 128, v0, v1, off + RO_BIAS, tag);
    };
    const int r = lane >> 2, q = lane & 3, g0 = ks * 8 + q, g1 = g0 + 4;
    const uint32_t gm = __shfl_sync(~0u, mm, ks);
    const uint32_t c2 = __popc(mm & 0x55u) | (__popc(mm & 0xAAu) << 16);
    const uint32_t tot = __reduce_add_sync(~0u, c2), pre = __reduce_add_sync(~0u, lane < ks ? c2 : 0u);
    const int ne = tot & 0xFFFF, no = tot >> 16;
    const uint32_t par = (q & 1) ? 0xAAu : 0x55u;
    const int base = (q & 1) ? pre >> 16 : pre & 0xFFFF;
    const int rk0 = base + __popc(gm & par & ((1u << q) - 1)), rk1 = base + __popc(gm & par & ((16u << q) - 1));
    uint32_t a[4], rs[4], x[4], w0, w1;
    zip4(lo[0], lo[1], hi[0], hi[1], x); split_pair(x, rk0 & 1, a[0], a[1], w0, rs[0], rs[1]);
    zip4(lo[2], lo[3], hi[2], hi[3], x); split_pair(x, rk1 & 1, a[2], a[3], w1, rs[2], rs[3]);
    pub128(true, scr + ((rb >> 2) * KSTEPS + ks) * 2048 + (rb & 3) * 512 + lane * 16, nonzero(a[0]), a[1], a[2], a[3]);
    w0 <<= 4 * q; w1 <<= 4 * q;
    w0 |= __shfl_xor_sync(~0u, w0, 1); w1 |= __shfl_xor_sync(~0u, w1, 1);
    w0 |= __shfl_xor_sync(~0u, w0, 2); w1 |= __shfl_xor_sync(~0u, w1, 2);
    if (q < 2) pub32(scr + SCR_M + (rb * KSTEPS + ks) * 64 + r * 8 + q * 4, q ? w1 : w0);
    const int em = min(ne, max(8, 16 - no)), om = min(no, 16 - em);
    const int odd = q & 1, m = odd ? om : em;
#pragma unroll
    for (int e = 0; e < 2; e++) {
        const int rk = e ? rk1 : rk0, t = 15 - rk;
        const int u = min(rk, t), in = (u >> 1) * 4 + (u & 1) + 2 * (odd ^ (rk >> 3 & 1)), out = 16 + (odd ? ne - em : 0) + rk - m;
        const int sl = rk >= m ? out : in;
        put_slot((gm >> (4 * e + q)) & 1, sl, rs[2 * e], rs[2 * e + 1], resid_off(e ? g1 : g0, rk & 1, r));
    }
    const int ntot = ne + no;
    const int ng = ntot > 16 ? (ntot + 3) >> 2 : min(4, (max(ne, no) + 1) >> 1);
    pub128(ks == 7 && q == 0, scr + SCR_I + rb * 128 + r * 16, ng | (units << 8), bias2.x, bias2.y, 0);
    const int idx = 2 * ks + (q & 1);
    const int frow = ks < 4 ? ks : ng - 1;
    const bool fill = ks < 4 ? !(idx < ((q >> 1) ? om : em) || (15 - idx) < ((q >> 1) ? em : om)) : ks == 4 && ng > 4 && 4 * frow + q >= ntot;
    put_slot(fill, frow * 4 + q, 0, 0, resid_off(q >> 1, q & 1, r));
}

template<int SEL> __device__ __forceinline__ void wgmma_sp(float (&d)[NACC], const uint32_t (&a)[4], uint64_t bdesc, uint32_t meta) {
    asm volatile("wgmma.mma_async.sp.sync.aligned.m64n48k32.f32.bf16.bf16 {%0, %1, %2, %3, %4, %5, %6, %7, %8, %9, %10, %11, %12, %13, %14, %15, %16, %17, %18, %19, %20, %21, %22, %23}, {%24, %25, %26, %27}, %28, %29, %30, 1, 1, 1, 0;"
        : "+f"(d[0]), "+f"(d[1]), "+f"(d[2]), "+f"(d[3]), "+f"(d[4]), "+f"(d[5]), "+f"(d[6]), "+f"(d[7]), "+f"(d[8]), "+f"(d[9]), "+f"(d[10]), "+f"(d[11]), "+f"(d[12]), "+f"(d[13]), "+f"(d[14]), "+f"(d[15]), "+f"(d[16]), "+f"(d[17]), "+f"(d[18]), "+f"(d[19]), "+f"(d[20]), "+f"(d[21]), "+f"(d[22]), "+f"(d[23])
        : "r"(a[0]), "r"(a[1]), "r"(a[2]), "r"(a[3]), "l"(bdesc), "r"(meta), "n"(SEL));
}
__device__ __forceinline__ void bar_sync(int id, int n) { asm volatile("bar.sync %0, %1;" :: "r"(id), "r"(n) : "memory"); }
__device__ __forceinline__ void bar_arrive(int id, int n) { asm volatile("bar.arrive %0, %1;" :: "r"(id), "r"(n) : "memory"); }

__device__ __forceinline__ void mbar_init(uint32_t bar, uint32_t cnt) { asm volatile("mbarrier.init.shared::cta.b64 [%0], %1;" :: "r"(bar), "r"(cnt) : "memory"); }
__device__ __forceinline__ void mbar_expect_tx(uint32_t bar, uint32_t bytes) {
    asm volatile("mbarrier.arrive.expect_tx.shared::cta.b64 _, [%0], %1;" :: "r"(bar), "r"(bytes) : "memory");
}
__device__ __forceinline__ void mbar_arrive(uint32_t bar) { asm volatile("mbarrier.arrive.shared::cta.b64 _, [%0];" :: "r"(bar) : "memory"); }
__device__ __forceinline__ void mbar_arrive_cluster(uint32_t bar) { asm volatile("mbarrier.arrive.shared::cluster.b64 _, [%0];" :: "r"(bar) : "memory"); }
__device__ __forceinline__ bool mbar_try(uint32_t bar, uint32_t parity) {
    uint32_t ok;
    asm volatile("{\n.reg .pred p;\nmbarrier.try_wait.parity.shared::cta.b64 p, [%1], %2;\nselp.u32 %0, 1, 0, p;\n}\n" : "=r"(ok) : "r"(bar), "r"(parity) : "memory");
    return ok;
}
__device__ __forceinline__ bool mbar_test(uint32_t bar, uint32_t parity) {
    uint32_t ok;
    asm volatile("{\n.reg .pred p;\nmbarrier.test_wait.parity.shared::cta.b64 p, [%1], %2;\nselp.u32 %0, 1, 0, p;\n}\n" : "=r"(ok) : "r"(bar), "r"(parity) : "memory");
    return ok;
}
__device__ __forceinline__ void fail_if(bool c) { asm volatile("{\n.reg .pred p;\nsetp.ne.u32 p, %0, 0;\n@p st.volatile.global.u32 [%1], %0;\n}\n" :: "r"((uint32_t)c), "l"(0ull) : "memory"); }
__device__ __forceinline__ void mbar_wait(uint32_t bar, uint32_t parity) {
    int n = 0;
    while (!mbar_try(bar, parity)) fail_if(++n > (1 << 20));
}
__device__ __forceinline__ void st_async(uint32_t addr, uint32_t v, uint32_t bar) {
    asm volatile("st.async.weak.shared::cluster.mbarrier::complete_tx::bytes.u32 [%0], %1, [%2];" :: "r"(addr), "r"(v), "r"(bar) : "memory");
}
__device__ __forceinline__ uint32_t mapa(uint32_t a, uint32_t cta) { uint32_t d; asm("mapa.shared::cluster.u32 %0, %1, %2;" : "=r"(d) : "r"(a), "r"(cta)); return d; }
__device__ __forceinline__ uint32_t lds32(uint32_t a) { uint32_t v; asm volatile("ld.shared.b32 %0, [%1];" : "=r"(v) : "r"(a)); return v; }
__device__ __forceinline__ uint32_t lds32v(uint32_t a) { uint32_t v; asm volatile("ld.volatile.shared.b32 %0, [%1];" : "=r"(v) : "r"(a) : "memory"); return v; }
__device__ __forceinline__ void sts32(uint32_t a, uint32_t v) { asm volatile("st.shared.b32 [%0], %1;" :: "r"(a), "r"(v) : "memory"); }
__device__ __forceinline__ uint32_t ld32(const void* a) { uint32_t v; asm volatile("ld.relaxed.gpu.global.u32 %0, [%1];" : "=r"(v) : "l"(a) : "memory"); return v; }
__device__ __forceinline__ uint4 ld128(const void* a) {
    uint4 v;
    asm volatile("{\n.reg .b64 s, t;\n.reg .b128 v;\nld.relaxed.gpu.global.L1::no_allocate.b128 v, [%4];\nmov.b128 {s, t}, v;\nmov.b64 {%0, %1}, s;\nmov.b64 {%2, %3}, t;\n}\n"
                 : "=r"(v.x), "=r"(v.y), "=r"(v.z), "=r"(v.w) : "l"(a) : "memory");
    return v;
}
__device__ __forceinline__ void ld128(const void* a, uint32_t (&v)[4]) { const uint4 t = ld128(a); v[0] = t.x; v[1] = t.y; v[2] = t.z; v[3] = t.w; }
__device__ __forceinline__ void ld128_if(bool c, const void* a, uint32_t& x, uint32_t& y, uint32_t& z, uint32_t& w) {
    asm volatile("{\n.reg .pred p;\n.reg .b64 s, t;\n.reg .b128 v;\nsetp.ne.u32 p, %5, 0;\nmov.b64 s, {%0, %1};\nmov.b64 t, {%2, %3};\nmov.b128 v, {s, t};\n"
                 "@p ld.relaxed.gpu.global.L1::no_allocate.b128 v, [%4];\nmov.b128 {s, t}, v;\nmov.b64 {%0, %1}, s;\nmov.b64 {%2, %3}, t;\n}\n"
                 : "+r"(x), "+r"(y), "+r"(z), "+r"(w) : "l"(a), "r"((uint32_t)c) : "memory");
}
__device__ __forceinline__ void ld32_if(bool c, const void* a, uint32_t& x) {
    asm volatile("{\n.reg .pred p;\nsetp.ne.u32 p, %2, 0;\n@p ld.relaxed.gpu.global.u32 %0, [%1];\n}\n" : "+r"(x) : "l"(a), "r"((uint32_t)c) : "memory");
}
__device__ __forceinline__ void mma_k8(float* c, uint2 a, uint32_t b) {
    asm volatile("mma.sync.aligned.m16n8k8.row.col.f32.bf16.bf16.f32 {%0,%1,%2,%3}, {%4,%5}, {%6}, {%0,%1,%2,%3};"
                 : "+f"(c[0]), "+f"(c[1]), "+f"(c[2]), "+f"(c[3]) : "r"(a.x), "r"(a.y), "r"(b));
}
__device__ __forceinline__ void mma_k16(float* d, uint2 a, uint2 a2, uint32_t b0, uint32_t b1, float c0, float c1, float c2, float c3) {
    asm volatile("mma.sync.aligned.m16n8k16.row.col.f32.bf16.bf16.f32 {%0,%1,%2,%3}, {%4,%5,%6,%7}, {%8,%9}, {%10,%11,%12,%13};"
                 : "=f"(d[0]), "=f"(d[1]), "=f"(d[2]), "=f"(d[3]) : "r"(a.x), "r"(a.y), "r"(a2.x), "r"(a2.y), "r"(b0), "r"(b1), "f"(c0), "f"(c1), "f"(c2), "f"(c3));
}
__device__ __forceinline__ uint32_t pack_bias(float lo, float hi, uint32_t bias2) {
    uint32_t p, o;
    asm("cvt.rn.bf16x2.f32 %0, %1, %2;" : "=r"(p) : "f"(hi), "f"(lo));
    asm("add.rn.bf16x2 %0, %1, %2;" : "=r"(o) : "r"(p), "r"(bias2));
    return o;
}

struct Params {
    const uint16_t* w; const uint16_t* bias; const uint8_t* x; uint4* scr; uint4* over;
    int ntok;
    int ntiles;
    int alltiles;
    int ncl;
    int nctas;
    int ne, pfd, pk;
    int ta, lead1, pw, k1, pfs, pfs2;
    int te, leade, slope1;
    int dl;
    uint32_t zero;
    int a, amagic, nfull;
};
constexpr int XEARLY = 1;
template <bool HELPER> __device__ __forceinline__ int place(const Params& p, int m) {
    if (HELPER) return ((m >> 1) * (p.a + 2) + ((m & 1) ? p.a + 1 : p.a >> 1));
    const int blk = (int)(((uint64_t)min(m, p.nfull) * (uint32_t)p.amagic) >> 32), r = m - blk * p.a;
    return (m + 2 * blk + (m < p.nfull && r >= (p.a >> 1)));
}

template <bool HELPER>
__global__ void __launch_bounds__(NTHREADS, 1)
spgemm_kernel(const __grid_constant__ CUtensorMap tmx, const __grid_constant__ CUtensorMap tmo, const Params p) {
    extern __shared__ unsigned char smem_raw[];
    const uint32_t sb = ((uint32_t)__cvta_generic_to_shared(smem_raw) + 1023u) & ~1023u;
    const int tid = threadIdx.x, warp = __shfl_sync(~0u, tid >> 5, 0), lane = tid & 31;
    const uint32_t tstart = now();
    const int rank = blockIdx.x % CL, cid = blockIdx.x / CL;
    const uint32_t bar_full = sb + OFF_FULL, bar_empty = sb + OFF_EMPTY, tk = sb + OFF_TK;
    uint4 wv[4];
    const int wrow = warp * 16 + (lane & 3) * 4;
    uint32_t b0, b1;
    auto prep_load = [&](int prb) {
        const uint32_t f0 = (prb >> 2) * 64;
        const uint16_t* const pa = p.w + ((uint32_t)(rank * 192 + wrow) * D + f0 + (lane >> 2) * 8);
#pragma unroll
        for (int j = 0; j < 4; j++) wv[j] = __ldg((const uint4*)(pa + j * D));
        b0 = __ldg(p.bias + (f0 + lane)); b1 = __ldg(p.bias + (f0 + 32 + lane));
    };
    if (!HELPER && warp < 12 && cid < 36) prep_load(cid);

    if (warp >= 12) {
        asm volatile("setmaxnreg.dec.sync.aligned.u32 32;");
        uint32_t epoch = 0;
        if (tid == NCONS + 32) asm volatile("ld.relaxed.gpu.global.u32 %0, [%1];" : "=r"(epoch) : "l"(&g_epoch) : "memory");
        if (tid == NCONS) {
#pragma unroll
            for (int s = 0; s < NSLOT; s++) { mbar_init(bar_full + 8 * s, 1); mbar_init(bar_empty + 8 * s, HELPER ? 3 : 3 * CL); }
            mbar_init(sb + OFF_MBAR, 1); mbar_init(sb + OFF_MBAR + 8, 1);
            mbar_init(sb + OFF_GO, 12); mbar_init(sb + OFF_EPOCH, 1);
            asm volatile("fence.mbarrier_init.release.cluster;" ::: "memory");
            mbar_expect_tx(sb + OFF_MBAR, 36 * 4);
            if (!HELPER) asm volatile("griddepcontrol.launch_dependents;");
            asm volatile("prefetch.tensormap [%0];" :: "l"(&tmo) : "memory");
            asm volatile("prefetch.tensormap [%0];" :: "l"(&tmx) : "memory");
        }
        __syncwarp();
        if (HELPER) asm volatile("bar.sync 0;" ::: "memory");
        else asm volatile("barrier.cluster.arrive.relaxed.aligned;\nbarrier.cluster.wait.aligned;" ::: "memory");
        uint64_t pol;
        asm volatile("createpolicy.fractional.L2::evict_first.b64 %0, 1.0;" : "=l"(pol));
        if (warp == 12) {
            const int ntiles = HELPER ? p.alltiles - p.ntiles : p.ntiles;
            if (!HELPER && rank != 0) {
                auto phys = [&](int m) { return m < ntiles ? place<false>(p, m) : p.alltiles; };
                auto prefetch = [&](int t) {
                    const int rows = min(NT, p.ntok - t * NT), r0 = rows * (rank - 1) / 2, r1 = rows * rank / 2;
                    if (lane == 0 && r1 > r0)
                        asm volatile("cp.async.bulk.prefetch.L2.global [%0], %1;" :: "l"(p.x + (size_t)t * TILE_BYTES + r0 * (D * 2)), "r"((r1 - r0) * (D * 2)) : "memory");
                };
                const int u0 = phys(XEARLY * p.ncl), n0 = phys(NSLOT * p.ncl + p.ne) - u0;
                for (int k = cid; k < n0; k += p.ncl) { wait_until(tstart + p.pfd + k * p.pk / p.ncl); prefetch(u0 + k); }
                const int ua = phys(p.ta), n1 = phys(p.ta + p.lead1) - ua;
                for (int k = cid; k < n1; k += p.ncl) { wait_until(tstart + p.pw + (min(k, p.k1) * p.pfs + max(k - p.k1, 0) * p.pfs2) / p.ncl); prefetch(ua + k); }
            } else {
                const uint32_t rtk = HELPER ? tk : mapa(tk, lane < CL ? lane : 0), rfull = HELPER ? bar_full : mapa(bar_full, lane < CL ? lane : 0);
                int s = 0; uint32_t ph = 1, drawn = 0;
                for (int j = 0;; j++) {
                    if (j == XEARLY) mbar_wait(sb + OFF_GO, 0);
                    mbar_wait(bar_empty + 8 * s, ph);
                    const int t = HELPER || j < NSLOT ? cid + j * p.ncl : (int)__shfl_sync(~0u, drawn, 0) + NSLOT * p.ncl;
                    const bool valid = t < ntiles;
                    if (valid && lane == 0) {
                        if (HELPER)
                            asm volatile("cp.async.bulk.tensor.4d.shared::cluster.global.mbarrier::complete_tx::bytes.L2::cache_hint [%0], [%1, {%3, %3, %3, %4}], [%2], %5;"
                                         :: "r"(sb + OFF_X + s * TILE_BYTES), "l"(&tmx), "r"(bar_full + 8 * s), "r"(0), "r"(place<HELPER>(p, t) * NB), "l"(pol) : "memory");
                        else
                            asm volatile("cp.async.bulk.tensor.4d.shared::cluster.global.mbarrier::complete_tx::bytes.multicast::cluster.L2::cache_hint [%0], [%1, {%3, %3, %3, %4}], [%2], %5, %6;"
                                         :: "r"(sb + OFF_X + s * TILE_BYTES), "l"(&tmx), "r"(bar_full + 8 * s), "r"(0), "r"(place<HELPER>(p, t) * NB), "h"((uint16_t)((1u << CL) - 1)), "l"(pol) : "memory");
                    }
                    if (HELPER) {
                        if (lane == 0) { sts32(tk + ((j & 7) << 2), valid ? (uint32_t)t : NO_TILE); mbar_expect_tx(bar_full + 8 * s, valid ? TILE_BYTES : 0); }
                    } else if (lane < CL) {
                        asm volatile("mbarrier.arrive.expect_tx.shared::cluster.b64 _, [%0], %1;" :: "r"(rfull + 8 * s), "r"(valid ? TILE_BYTES + 4 : 4) : "memory");
                        st_async(rtk + ((j & 7) << 2), valid ? (uint32_t)t : NO_TILE, rfull + 8 * s);
                    }
                    if (!valid) break;
                    if (!HELPER && lane == 0 && t > p.ta) {
                        auto fr = [&](int m) { const int f = m + p.leade + max(0, (p.slope1 * (p.te - m)) >> 16); return f < ntiles ? place<false>(p, f) : p.alltiles; };
                        const int u1 = fr(t);
                        for (int u = fr(t - 1); u < u1; u++)
                            asm volatile("cp.async.bulk.prefetch.L2.global [%0], %1;" :: "l"(p.x + (size_t)u * TILE_BYTES), "r"(min(NT, p.ntok - u * NT) * (D * 2)) : "memory");
                    }
                    if (!HELPER && lane == 0 && j >= NSLOT - 1) drawn = atomicInc(&g_ticket, ntiles - p.ncl * (NSLOT - 1) - 1);
                    if (++s == NSLOT) { s = 0; ph ^= 1; }
                }
            }
        } else {
            const int g = warp - 13;
            const uint32_t rempty = HELPER ? bar_empty : mapa(bar_empty, 0);
            if (g == 0 && lane == 0) { sts32(sb + OFF_EPOCH + 8, epoch); mbar_arrive(sb + OFF_EPOCH); }
            mbar_wait(bar_full, 0);
            uint32_t t = lds32v(tk), ph = 0;
            int s = 0;
            for (int i = 0;; i++) {
                bar_sync(BAR_SFULL + g, 160);
                const int s1 = s + 1 == NSLOT ? 0 : s + 1;
                if (s1 == 0) ph ^= 1;
                if (lane == 0) { if (HELPER) mbar_arrive(bar_empty + 8 * s); else mbar_arrive_cluster(rempty + 8 * s); }
                const bool ready = __all_sync(~0u, mbar_test(bar_full + 8 * s1, ph));
                if (ready) bar_arrive(BAR_G + g, 288);
                if (lane == 0) {
                    asm volatile("fence.proxy.async.shared::cta;" ::: "memory");
                    asm volatile("cp.async.bulk.tensor.2d.global.shared::cta.bulk_group.L2::cache_hint [%0, {%2, %3}], [%1], %4;"
                                 :: "l"(&tmo), "r"(sb + OFF_STG + g * STG_BYTES), "r"((g * 3 + rank) * 64), "r"((place<HELPER>(p, t)) * NT), "l"(pol) : "memory");
                    asm volatile("cp.async.bulk.commit_group;" ::: "memory");
                    if (g == 2 && i == 0 && atomicInc(&g_passed, p.nctas - 1) == (uint32_t)p.nctas - 1) atomicAdd(&g_epoch, 1);
                }
                __syncwarp();
                s = s1;
                if (!ready) { mbar_wait(bar_full + 8 * s, ph); bar_arrive(BAR_G + g, 288); }
                t = lds32v(tk + (((i + 1) & 7) << 2));
                if (lane == 0) asm volatile("cp.async.bulk.wait_group.read 0;" ::: "memory");
                __syncwarp();
                if (t == NO_TILE) break;
                bar_arrive(BAR_SEMPTY + g, 160);
            }
        }
        __syncwarp();
        if (!HELPER) asm volatile("barrier.cluster.arrive.relaxed.aligned;\nbarrier.cluster.wait.aligned;" ::: "memory");
    } else {
        asm volatile("setmaxnreg.inc.sync.aligned.u32 160;");
        const int wg = warp >> 2, r = lane >> 2, q = lane & 3;
        uint32_t epoch;
        if (HELPER) asm volatile("bar.sync 0;" ::: "memory");
        else {
            int prb = cid;
            asm volatile("barrier.cluster.arrive.relaxed.aligned;" ::: "memory");
            if (prb >= 36) asm volatile("barrier.cluster.wait.aligned;" ::: "memory");
#pragma unroll 1
            for (int round = 0; prb < 36; prb += p.ncl, round++) {
                const uint32_t wsm = sb + OFF_WST, msk = sb + OFF_MSK + (round & 1) * 144, mbar = sb + OFF_MBAR + (round & 1) * 8;
                if (round) {
                    bar_sync(3, 384);
                    if (tid == 0) mbar_expect_tx(mbar, 36 * 4);
                    prep_load(prb);
                }
                const uint32_t mk = __ballot_sync(~0u, has_tie(wv[0].x, wv[1].x, wv[2].x, wv[3].x) || has_tie(wv[0].y, wv[1].y, wv[2].y, wv[3].y) ||
                                                       has_tie(wv[0].z, wv[1].z, wv[2].z, wv[3].z) || has_tie(wv[0].w, wv[1].w, wv[2].w, wv[3].w));
                if (round == 0) asm volatile("barrier.cluster.wait.aligned;" ::: "memory");
                if (lane < CL) st_async(mapa(msk + (rank * 12 + warp) * 4, lane), mk, mapa(mbar, lane));
#pragma unroll
                for (int j = 0; j < 4; j++) {
                    const int row = wrow + j;
                    const uint32_t ad = wsm + row * 128 + (((lane >> 2) ^ ((row & 1) | ((row >> 1) & 6))) << 4);
                    asm volatile("st.shared.v4.b32 [%0], {%1,%2,%3,%4};" :: "r"(ad), "r"(wv[j].x), "r"(wv[j].y), "r"(wv[j].z), "r"(wv[j].w) : "memory");
                }
                if (warp >= 6) bar_arrive(1, 384);
                else {
                    bar_sync(1, 384);
                    mbar_wait(sb + OFF_EPOCH, 0);
                    epoch = lds32v(sb + OFF_EPOCH + 8);
                    uint8_t* const scr = (uint8_t*)p.scr + (epoch & 1) * SCR_END;
                    mbar_wait(mbar, (round >> 1) & 1);
                    uint32_t m0 = 0, m1 = 0;
                    if (lane < KSTEPS) asm volatile("ld.volatile.shared.v2.b32 {%0,%1}, [%2];" : "=r"(m0), "=r"(m1) : "r"(msk + 8 * lane) : "memory");
                    uint32_t c0 = m0 - ((m0 >> 1) & 0x55555555u), c1 = m1 - ((m1 >> 1) & 0x55555555u);
                    c0 = (c0 & 0x33333333u) + ((c0 >> 2) & 0x33333333u) + (c1 & 0x33333333u) + ((c1 >> 2) & 0x33333333u);
                    c1 = __reduce_add_sync(~0u, (c0 >> 4) & 0x0F0F0F0Fu); c0 = __reduce_add_sync(~0u, c0 & 0x0F0F0F0Fu);
                    auto key = [&](int v) { return ((((v & 1) ? c1 : c0) >> (4 * (v & 6))) & 0xFFu) * 8 + v; };
                    const uint32_t ku = key(lane & 7);
                    const uint32_t l0 = __ballot_sync(~0u, key(lane >> 3) < ku), l1 = __ballot_sync(~0u, key(4 + (lane >> 3)) < ku);
                    const int rk = __popc((l0 >> (lane & 7)) & 0x01010101u) + __popc((l1 >> (lane & 7)) & 0x01010101u);
                    const int pp = prb & 3;
                    const int ulo = __ffs(__ballot_sync(~0u, rk == pp)) - 1, uhi = __ffs(__ballot_sync(~0u, rk == 7 - pp)) - 1;
                    uint32_t lo[4], hi[4];
                    load_unit(wsm, warp, ulo, lane, lo); load_unit(wsm, warp, uhi, lane, hi);
                    const uint32_t mm = (((m0 >> (4 * ulo)) | (m0 >> (4 * uhi))) & 15u) | ((((m1 >> (4 * ulo)) | (m1 >> (4 * uhi))) & 15u) << 4);
                    const uint2 bias2 = make_uint2(__shfl_sync(~0u, ulo < 4 ? b0 : b1, (ulo * 8 + r) & 31) * 0x10001u, __shfl_sync(~0u, uhi < 4 ? b0 : b1, (uhi * 8 + r) & 31) * 0x10001u);
                    emit_step(lo, hi, mm, prb, rank * 6 + warp, lane, ulo | (uhi << 4), bias2, scr, p.over, epoch + 1);
                }
            }
            if (cid >= 36 || warp >= 6) { mbar_wait(sb + OFF_EPOCH, 0); epoch = lds32v(sb + OFF_EPOCH + 8); }
            if (warp >= 6) for (int i = blockIdx.x * 192 + tid - 192; i < SCR_END / 16; i += gridDim.x * 192) p.scr[(~epoch & 1) * (SCR_END / 16) + i] = make_uint4(0, 0, 0, 0);
        }
        if (HELPER) { mbar_wait(sb + OFF_EPOCH, 0); epoch = lds32v(sb + OFF_EPOCH + 8); }
        if (wg == 2) bar_arrive(BAR_T, 256);
        const int mt = wg * 3 + rank, rb = mt * 4 + (warp & 3);
        const uint8_t* const scr = (const uint8_t*)p.scr + (epoch & 1) * SCR_END;
        const uint8_t* const fp = scr + mt * KSTEPS * 2048 + (warp & 3) * 512 + lane * 16;
        if (!HELPER && cid < 36) bar_sync(2, 384);
        if (!HELPER && cid < 36 && p.ncl >= 36) wait_until(now() + p.dl);
        else for (int n = 0; __any_sync(~0u, ld32(fp + 17 * 2048) == 0); n++) fail_if(n > (1 << 22));
        uint32_t a[KSTEPS][4], meta[9];
        uint2 rv[4]; uint32_t ro[4];
        uint32_t info, bias_lo, bias_hi;
        {
            const uint8_t* const ip = scr + SCR_I + rb * 128 + r * 16;
            const uint8_t* const sp = scr + SCR_S + rb * 2048 + q * 128 + r * 16;
            const uint8_t* const mp = scr + SCR_M + (rb * KSTEPS + (q >> 1)) * 64 + r * 8 + (q & 1) * 4;
            uint4 i0 = ld128(ip), sv[4];
#pragma unroll
            for (int j = 0; j < 4; j++) sv[j] = ld128(sp + j * 512);
#pragma unroll
            for (int j = 0; j < 9; j++) meta[j] = ld32(mp + j * 128);
#pragma unroll
            for (int k = 0; k < KSTEPS; k++) ld128(fp + k * 2048, a[k]);
            if (lane == 0) mbar_arrive(sb + OFF_GO);
            for (int n = 0;; n++) {
                uint32_t lo = __vimin3_u32(__vimin3_u32(i0.x, meta[8], sv[0].z), sv[1].z, min(sv[2].z, sv[3].z));
#pragma unroll
                for (int j = 0; j < 8; j += 2) lo = __vimin3_u32(lo, meta[j], meta[j + 1]);
#pragma unroll
                for (int k = 0; k < KSTEPS; k += 2) lo = __vimin3_u32(lo, a[k][0], a[k + 1][0]);
                if (__all_sync(~0u, lo != 0)) break;
                fail_if(n > (1 << 20));
                ld128_if(i0.x == 0, ip, i0.x, i0.y, i0.z, i0.w);
#pragma unroll
                for (int j = 0; j < 4; j++) ld128_if(sv[j].z == 0, sp + j * 512, sv[j].x, sv[j].y, sv[j].z, sv[j].w);
#pragma unroll
                for (int j = 0; j < 9; j++) ld32_if(meta[j] == 0, mp + j * 128, meta[j]);
#pragma unroll
                for (int k = 0; k < KSTEPS; k++) ld128_if(a[k][0] == 0, fp + k * 2048, a[k][0], a[k][1], a[k][2], a[k][3]);
            }
            info = i0.x; bias_lo = i0.y; bias_hi = i0.z;
#pragma unroll
            for (int j = 0; j < 4; j++) { rv[j] = make_uint2(sv[j].x, sv[j].y); ro[j] = sv[j].z; }
        }
#pragma unroll
        for (int j = 0; j < 4; j++) { rv[j].x ^= p.zero; rv[j].y ^= p.zero; }
        info = __shfl_sync(~0u, info, 0);
        const int ngrp = info & 0xFF, ulo = (info >> 8) & 7, uhi = (info >> 12) & 7;
#pragma unroll 1
        for (int j = 4; j < ngrp; j++)
            for (int n = 0; __any_sync(~0u, ld128(p.over + (rb * 144 + j * 4 + q) * 8 + r).w != epoch + 1); n++) fail_if(n > (1 << 20));
        mbar_wait(bar_full, 0);
        const uint32_t stg = sb + OFF_STG + wg * STG_BYTES + ((lane >> 4) * 8 + (lane & 7)) * 128 + (((((lane >> 3) & 1) ? uhi : ulo) ^ (lane & 7)) << 4);
        float acc[NACC];
        uint32_t bq[NB][2];
        auto gather = [&](uint32_t xb) {
#pragma unroll
            for (int j = 0; j < 4; j++) {
                if (j < ngrp) {
#pragma unroll
                    for (int n = 0; n < NB; n++) { uint32_t v = lds32(xb + ro[j] + (n * 9216 - RO_BIAS)); if (j < 2) acc[4 * n + j] = __uint_as_float(v); else bq[n][j - 2] = v; }
                } else {
#pragma unroll
                    for (int n = 0; n < NB; n++) { if (j < 2) acc[4 * n + j] = 0.f; else bq[n][j - 2] = 0; }
                }
            }
        };
        gather(sb + OFF_X);
        bar_sync(BAR_T + wg, 256);
        int s = 0;
        bool more = true;
        for (int i = 0; more; i++) {
            const uint32_t xb = sb + OFF_X + s * TILE_BYTES;
            s = s + 1 == NSLOT ? 0 : s + 1;
#pragma unroll
            for (int n = 0; n < NB; n++) mma_k16(acc + 4 * n, rv[0], rv[1], __float_as_uint(acc[4 * n]), __float_as_uint(acc[4 * n + 1]), 0.f, 0.f, 0.f, 0.f);
#pragma unroll
            for (int n = 0; n < NB; n++) mma_k16(acc + 4 * n, rv[2], rv[3], bq[n][0], bq[n][1], acc[4 * n], acc[4 * n + 1], acc[4 * n + 2], acc[4 * n + 3]);
#pragma unroll 1
            for (int j = 4; j < ngrp; j++) {
                const uint4 o = __ldca(p.over + (rb * 144 + j * 4 + q) * 8 + r); const uint2 v = make_uint2(o.x, o.y); const uint32_t off = o.z - RO_BIAS;
#pragma unroll
                for (int n = 0; n < NB; n++) bq[n][0] = lds32(xb + off + n * 9216);
#pragma unroll
                for (int n = 0; n < NB; n++) mma_k8(acc + 4 * n, v, bq[n][0]);
            }
            const uint64_t desc = ((uint64_t)1 << 62) | ((uint64_t)(9216 >> 4) << 32) | ((uint64_t)1 << 16) | (uint64_t)(xb >> 4);
            asm volatile("wgmma.fence.sync.aligned;" ::: "memory");
#pragma unroll
            for (int k = 0; k < KSTEPS; k++) {
                const uint64_t d = desc + (uint64_t)(((k >> 1) * 1024 + (k & 1) * 64) >> 4);
                if (k & 1) wgmma_sp<1>(acc, a[k], d, meta[k >> 1]);
                else       wgmma_sp<0>(acc, a[k], d, meta[k >> 1]);
                if (k == SPLIT - 1) asm volatile("wgmma.commit_group.sync.aligned;" ::: "memory");
            }
            asm volatile("wgmma.commit_group.sync.aligned;" ::: "memory");
            bar_arrive(wg == 2 ? BAR_T : BAR_T + 1 + wg, 256);
            asm volatile("wgmma.wait_group.sync.aligned 1;" ::: "memory");
            if (wg != 0 || i != 0) bar_arrive(wg == 0 ? BAR_G + 2 : BAR_G - 1 + wg, 288);
            if (i != 0) bar_sync(BAR_SEMPTY + wg, 160);
            asm volatile("wgmma.wait_group.sync.aligned 0;" ::: "memory");
#pragma unroll
            for (int n = 0; n + 1 < NB; n += 2) {
                const uint32_t p0 = pack_bias(acc[4 * n], acc[4 * n + 1], bias_lo), p1 = pack_bias(acc[4 * n + 2], acc[4 * n + 3], bias_hi);
                const uint32_t p2 = pack_bias(acc[4 * n + 4], acc[4 * n + 5], bias_lo), p3 = pack_bias(acc[4 * n + 6], acc[4 * n + 7], bias_hi);
                asm volatile("stmatrix.sync.aligned.m8n8.x4.trans.shared.b16 [%0], {%1,%2,%3,%4};" :: "r"(stg + n * 1024), "r"(p0), "r"(p1), "r"(p2), "r"(p3) : "memory");
            }
            if (NB & 1) {
                const uint32_t p0 = pack_bias(acc[NACC - 4], acc[NACC - 3], bias_lo), p1 = pack_bias(acc[NACC - 2], acc[NACC - 1], bias_hi);
                asm volatile("stmatrix.sync.aligned.m8n8.x2.trans.shared.b16 [%0], {%1,%2};" :: "r"(stg + (NB - 1) * 1024), "r"(p0), "r"(p1) : "memory");
            }
            bar_arrive(BAR_SFULL + wg, 160);
            bar_sync(BAR_G + wg, 288);
            const uint32_t tn = lds32v(tk + (((i + 1) & 7) << 2));
            gather(sb + OFF_X + s * TILE_BYTES);
            more = __any_sync(~0u, tn != NO_TILE);
            if (more || wg == 0) bar_sync(BAR_T + wg, 256);
        }
        if (wg == 0) bar_arrive(BAR_G + 2, 288);
        __syncwarp();
        if (!HELPER) asm volatile("barrier.cluster.arrive.relaxed.aligned;\nbarrier.cluster.wait.aligned;" ::: "memory");
    }
}

typedef CUresult (*EncodeFn)(CUtensorMap*, CUtensorMapDataType, cuuint32_t, void*, const cuuint64_t*, const cuuint64_t*, const cuuint32_t*, const cuuint32_t*,
                             CUtensorMapInterleave, CUtensorMapSwizzle, CUtensorMapL2promotion, CUtensorMapFloatOOBfill);

extern "C" void kernel_launch(void* const* d_in, const int* in_sizes, int n_in, void* d_out, int out_size) {
    static EncodeFn enc = nullptr;
    static int ncl = 0, nhelp = 0;
    const int ntok = in_sizes[0] / D;
    cudaLaunchConfig_t cfg = {};
    cudaLaunchAttribute at[1];
    at[0].id = cudaLaunchAttributeClusterDimension; at[0].val.clusterDim.x = CL; at[0].val.clusterDim.y = 1; at[0].val.clusterDim.z = 1;
    cfg.blockDim = dim3(NTHREADS); cfg.dynamicSmemBytes = SMEM_BYTES; cfg.attrs = at; cfg.numAttrs = 1; cfg.stream = cudaStreamPerThread;
    if (!enc) {
        cudaDriverEntryPointQueryResult qr; void* fn = nullptr;
        cudaGetDriverEntryPoint("cuTensorMapEncodeTiled", &fn, cudaEnableDefault, &qr);
        enc = (EncodeFn)fn;
        cudaFuncSetAttribute(spgemm_kernel<false>, cudaFuncAttributeMaxDynamicSharedMemorySize, SMEM_BYTES);
        cudaFuncSetAttribute(spgemm_kernel<true>, cudaFuncAttributeMaxDynamicSharedMemorySize, SMEM_BYTES);
        int dev = 0, nsm = 0;
        cudaGetDevice(&dev);
        cudaDeviceGetAttribute(&nsm, cudaDevAttrMultiProcessorCount, dev);
        cfg.gridDim = dim3(CL * (nsm / CL));
        cudaOccupancyMaxActiveClusters(&ncl, spgemm_kernel<false>, &cfg);
        if (ncl < 1) ncl = 1;
        nhelp = nsm > CL * ncl ? (nsm - CL * ncl) / CL : 0;
    }
    CUtensorMap tmx, tmo;
    {
        cuuint64_t dims[4] = {64, 8, 9, (cuuint64_t)(ntok / 8)};
        cuuint64_t strides[3] = {D * 2, 128, 8 * D * 2};
        cuuint32_t box[4] = {64, 8, 9, NB}, es[4] = {1, 1, 1, 1};
        enc(&tmx, CU_TENSOR_MAP_DATA_TYPE_BFLOAT16, 4, d_in[0], dims, strides, box, es, CU_TENSOR_MAP_INTERLEAVE_NONE,
            CU_TENSOR_MAP_SWIZZLE_128B, CU_TENSOR_MAP_L2_PROMOTION_L2_128B, CU_TENSOR_MAP_FLOAT_OOB_FILL_NONE);
    }
    {
        cuuint64_t dims[2] = {D, (cuuint64_t)ntok};
        cuuint64_t strides[1] = {D * 2};
        cuuint32_t box[2] = {64, NT}, es[2] = {1, 1};
        enc(&tmo, CU_TENSOR_MAP_DATA_TYPE_BFLOAT16, 2, d_out, dims, strides, box, es, CU_TENSOR_MAP_INTERLEAVE_NONE,
            CU_TENSOR_MAP_SWIZZLE_128B, CU_TENSOR_MAP_L2_PROMOTION_NONE, CU_TENSOR_MAP_FLOAT_OOB_FILL_NONE);
    }
    Params p;
    p.w = (const uint16_t*)d_in[1]; p.bias = (const uint16_t*)d_in[2]; p.x = (const uint8_t*)d_in[0];
    p.ntok = ntok;
    cudaGetSymbolAddress((void**)&p.scr, g_scr); cudaGetSymbolAddress((void**)&p.over, g_over);
    p.zero = 0;
    p.alltiles = (ntok + NT - 1) / NT;
    const int nc = ncl < p.alltiles ? ncl : p.alltiles;
    p.a = nhelp ? (int)(2 * nc / (nhelp * 1.07) + 0.5) : 2;
    if (p.a < 2) p.a = 2;
    const int nblk = (int)(p.alltiles / (p.a + 2) * 0.6);
    const int nh = nhelp && 2 * nblk >= nhelp && p.alltiles - 2 * nblk >= nc ? nhelp : 0;
    p.ntiles = p.alltiles - (nh ? 2 * nblk : 0);
    p.nfull = nh ? nblk * p.a : 0; p.amagic = (int)(0xFFFFFFFFu / (uint32_t)p.a + 1);
    p.ncl = nc; p.nctas = CL * (nc + nh);
    auto tiles = [](double v) { return (int)(v * 56 / NT); };
    auto ns = [](double v) { return (int)(v * NT / 56); };
    p.ne = tiles(40); p.pfd = 1200; p.pk = ns(1200);
    p.ta = (int)(p.ntiles * 0.4) + 1; p.lead1 = tiles(250); p.pw = 2500;
    p.k1 = tiles(78); p.pfs = ns(700); p.pfs2 = ns(2000);
    p.te = (int)(p.ntiles * 1.0) + 2; p.leade = tiles(40); p.slope1 = ((p.lead1 - p.leade) << 16) / (p.te - p.ta);
    p.dl = 200;
    cfg.gridDim = dim3(CL * nc);
    cudaLaunchKernelEx(&cfg, spgemm_kernel<false>, tmx, tmo, p);
    if (nh) {
        at[0].id = cudaLaunchAttributeProgrammaticStreamSerialization; at[0].val.programmaticStreamSerializationAllowed = 1;
        cfg.gridDim = dim3(CL * nh);
        p.ncl = nh;
        cudaLaunchKernelEx(&cfg, spgemm_kernel<true>, tmx, tmo, p);
    }
}
```

```cpp
#include <cuda_runtime.h>
#include <cuda_bf16.h>
#include <cuda.h>
#include <stdint.h>

constexpr int D = 576;
constexpr int NH = 2;
constexpr int NT = 48;
constexpr int NSLOT = 3;
constexpr int SPLIT = 13;
constexpr int KSTEPS = 18;
constexpr int CL = 3;
constexpr int TILE_BYTES = NT * D * 2;
constexpr int STG_BYTES = NT * 128;
constexpr int NACC = NT / 2;
constexpr int NB = NT / 8;
constexpr int NCONS = 384;
constexpr int NTHREADS = 512;
constexpr uint32_t NO_TILE = 0xFFFFFFFFu;

constexpr int OFF_X = 0;
constexpr int OFF_STG = OFF_X + NSLOT * TILE_BYTES;
constexpr int OFF_WST = OFF_STG;
constexpr int OFF_FULL = OFF_STG + ((1 + NH) * 3 * STG_BYTES > 50176 ? (1 + NH) * 3 * STG_BYTES : 50176);
constexpr int OFF_EMPTY = OFF_FULL + 8 * NSLOT;
constexpr int OFF_MBAR = OFF_EMPTY + 8 * NSLOT;
constexpr int OFF_GO = OFF_MBAR + 16;
constexpr int OFF_FB = OFF_GO + 16;
constexpr int OFF_EPOCH = OFF_FB + 24;
constexpr int OFF_TK = OFF_EPOCH + 16;
constexpr int OFF_MSK = OFF_TK + 32;
constexpr int SMEM_BYTES = OFF_MSK + 2 * 36 * 4 + 1024;
static_assert(SMEM_BYTES <= 232448 && NSLOT < 8 && NSLOT >= 3, "layout");
constexpr int BAR_T = 4, BAR_SFULL = 7, BAR_SEMPTY = 10, BAR_G = 13;

constexpr int BLK_M = KSTEPS * 2048, BLK_S = BLK_M + 4 * KSTEPS * 64, BLK_I = BLK_S + 4 * 2048, BLK = BLK_I + 4 * 128, SCR_END = 9 * BLK;
static_assert(BLK <= TILE_BYTES && BLK <= OFF_FULL - OFF_STG, "fragment blocks");
__device__ __align__(128) uint4    g_scr[2][SCR_END / 16];
__device__ __align__(128) uint4    g_over[36 * 144 * 8];
__device__ __align__(128) uint32_t g_epoch;
__device__ __align__(128) uint32_t g_passed;
__device__ __align__(128) uint32_t g_ticket;

__device__ __forceinline__ uint32_t now() { uint32_t c; asm volatile("mov.u32 %0, %%globaltimer_lo;" : "=r"(c)); return c; }
__device__ __forceinline__ void wait_until(uint32_t due) { while ((int)(now() - due) < 0) __nanosleep(20); }

__device__ __forceinline__ uint32_t max2(uint32_t a, uint32_t b) { uint32_t d; asm("max.u16x2 %0, %1, %2;" : "=r"(d) : "r"(a), "r"(b)); return d; }
__device__ __forceinline__ uint32_t min2(uint32_t a, uint32_t b) { uint32_t d; asm("min.u16x2 %0, %1, %2;" : "=r"(d) : "r"(a), "r"(b)); return d; }
__device__ __forceinline__ uint32_t sign2(uint32_t a) { uint32_t d; asm("prmt.b32 %0, %1, %1, 0xBB99;" : "=r"(d) : "r"(a)); return d; }
__device__ __forceinline__ void zip4(uint32_t a01, uint32_t a23, uint32_t b01, uint32_t b23, uint32_t (&x)[4]) {
    x[0] = __byte_perm(a01, b01, 0x5410); x[1] = __byte_perm(a01, b01, 0x7632); x[2] = __byte_perm(a23, b23, 0x5410); x[3] = __byte_perm(a23, b23, 0x7632);
}
__device__ __forceinline__ void middle2(const uint32_t (&x)[4], uint32_t (&m)[4], uint32_t& u, uint32_t& v) {
#pragma unroll
    for (int i = 0; i < 4; i++) m[i] = x[i] & 0x7FFF7FFFu;
    u = min2(max2(m[0], m[1]), max2(m[2], m[3])); v = max2(min2(m[0], m[1]), min2(m[2], m[3]));
}
__device__ __forceinline__ bool has_tie(uint32_t x0, uint32_t x1, uint32_t x2, uint32_t x3) {
    const uint32_t x[4] = {x0, x1, x2, x3};
    uint32_t m[4], u, v;
    middle2(x, m, u, v);
    const uint32_t t = u ^ v;
    return ((t & 0xFFFFu) == 0 && (v & 0xFFFFu) != 0) || (t < 0x10000u && v >= 0x10000u);
}
__device__ __forceinline__ void load_unit(uint32_t wsm, int ls, int unit, int lane, uint32_t (&m)[4]) {
    const int row = ls * 32 + (lane >> 4) * 16 + ((lane & 7) >> 1) * 4 + ((lane >> 3) & 1) * 2 + (lane & 1);
    const uint32_t ad = wsm + row * 128 + ((unit ^ ((row & 1) | ((row >> 1) & 6))) << 4);
    asm volatile("ldmatrix.sync.aligned.m8n8.x4.trans.shared.b16 {%0,%1,%2,%3}, [%4];" : "=r"(m[0]), "=r"(m[1]), "=r"(m[2]), "=r"(m[3]) : "r"(ad) : "memory");
}
__device__ __forceinline__ void split_pair(const uint32_t (&x)[4], bool P, uint32_t& alo, uint32_t& ahi, uint32_t& nib, uint32_t& rlo, uint32_t& rhi) {
    uint32_t m[4], u, v;
    middle2(x, m, u, v);
    const uint32_t c = 0x80008000u - max2(max2(u, v), 0x00010001u);
    uint32_t k0 = sign2(m[0] + c), k1 = sign2(m[1] + c), k2 = sign2(m[2] + c), k3 = sign2(m[3] + c);
    const uint32_t three = (k0 & k1 & (k2 | k3)) | (k2 & k3 & (k0 | k1)), four = k0 & k1 & k2 & k3;
    const uint32_t pa = P ? k2 : k0, pb = P ? k3 : k1;
    const uint32_t ra = three & pa, rb = three & pb & (four | ~pa);
    const uint32_t va = (P ? x[2] : x[0]) & ra, vb = (P ? x[3] : x[1]) & rb;
    if (P) { k2 &= ~ra; k3 &= ~rb; } else { k0 &= ~ra; k1 &= ~rb; }
    const uint32_t s1 = k1 & k0, s2 = k2 & (k0 | k1);
    const uint32_t t = (k1 & x[1]) | (~k1 & k2 & x[2]);
    const uint32_t x0 = (k0 & x[0]) | (~k0 & t), x1 = (s1 & x[1]) | (s2 & x[2]) | (k3 & x[3]);
    nib = (~k0 & k1 & 0x00010001u) | (~k0 & ~k1 & 0x00020002u) | (~s2 & 0x00040004u) | (~s1 & 0x00080008u);
    alo = __byte_perm(x0, x1, 0x5410); ahi = __byte_perm(x0, x1, 0x7632);
    rlo = __byte_perm(va, vb, 0x5410); rhi = __byte_perm(va, vb, 0x7632);
}
__device__ __forceinline__ uint32_t nonzero(uint32_t v) { return v ? v : 0x8000u; }
__device__ __forceinline__ void pub32(void* a, uint32_t v) { asm volatile("st.relaxed.gpu.global.u32 [%0], %1;" :: "l"(a), "r"(v) : "memory"); }
__device__ __forceinline__ void pub128(bool c, void* a, uint32_t x, uint32_t y, uint32_t z, uint32_t w) {
    asm volatile("{\n.reg .pred p;\n.reg .b64 s, t;\n.reg .b128 v;\nsetp.ne.u32 p, %5, 0;\nmov.b64 s, {%1, %2};\nmov.b64 t, {%3, %4};\nmov.b128 v, {s, t};\n@p st.relaxed.gpu.global.b128 [%0], v;\n}\n"
                 :: "l"(a), "r"(x), "r"(y), "r"(z), "r"(w), "r"((uint32_t)c) : "memory");
}
constexpr int RO_BIAS = 16;
__device__ __forceinline__ uint32_t resid_off(int g, int P, int r) {
    int k0 = 4 * g + 2 * P;
    int chunk = k0 >> 6, byte = (k0 & 63) * 2;
    return chunk * 1024 + r * 128 + (((byte >> 4) ^ r) << 4) + (byte & 15);
}
__device__ __forceinline__ void emit_step(const uint32_t (&lo)[4], const uint32_t (&hi)[4], uint32_t mm, int rb, int ks, int lane, uint32_t units, uint2 bias2,
                                          uint8_t* scr, uint4* over, uint32_t tag) {
    scr += (rb >> 2) * BLK;
    const int wp = rb & 3;
    uint8_t* const s0 = scr + BLK_S + wp * 2048 + (lane >> 2) * 16;
    uint8_t* const s1 = (uint8_t*)(over + rb * 144 * 8 + (lane >> 2));
    auto put_slot = [&](bool c, int sl, uint32_t v0, uint32_t v1, uint32_t off) {
        pub128(c, (sl < 16 ? s0 : s1) + sl * 128, v0, v1, off + RO_BIAS, tag);
    };
    const int r = lane >> 2, q = lane & 3, g0 = ks * 8 + q, g1 = g0 + 4;
    const uint32_t gm = __shfl_sync(~0u, mm, ks);
    const uint32_t c2 = __popc(mm & 0x55u) | (__popc(mm & 0xAAu) << 16);
    const uint32_t tot = __reduce_add_sync(~0u, c2), pre = __reduce_add_sync(~0u, lane < ks ? c2 : 0u);
    const int ne = tot & 0xFFFF, no = tot >> 16;
    const uint32_t par = (q & 1) ? 0xAAu : 0x55u;
    const int base = (q & 1) ? pre >> 16 : pre & 0xFFFF;
    const int rk0 = base + __popc(gm & par & ((1u << q) - 1)), rk1 = base + __popc(gm & par & ((16u << q) - 1));
    uint32_t a[4], rs[4], x[4], w0, w1;
    zip4(lo[0], lo[1], hi[0], hi[1], x); split_pair(x, rk0 & 1, a[0], a[1], w0, rs[0], rs[1]);
    zip4(lo[2], lo[3], hi[2], hi[3], x); split_pair(x, rk1 & 1, a[2], a[3], w1, rs[2], rs[3]);
    pub128(true, scr + ks * 2048 + wp * 512 + lane * 16, nonzero(a[0]), a[1], a[2], a[3]);
    w0 <<= 4 * q; w1 <<= 4 * q;
    w0 |= __shfl_xor_sync(~0u, w0, 1); w1 |= __shfl_xor_sync(~0u, w1, 1);
    w0 |= __shfl_xor_sync(~0u, w0, 2); w1 |= __shfl_xor_sync(~0u, w1, 2);
    if (q < 2) pub32(scr + BLK_M + (wp * KSTEPS + ks) * 64 + r * 8 + q * 4, q ? w1 : w0);
    const int em = min(ne, max(8, 16 - no)), om = min(no, 16 - em);
    const int odd = q & 1, m = odd ? om : em;
#pragma unroll
    for (int e = 0; e < 2; e++) {
        const int rk = e ? rk1 : rk0, t = 15 - rk;
        const int u = min(rk, t), in = (u >> 1) * 4 + (u & 1) + 2 * (odd ^ (rk >> 3 & 1)), out = 16 + (odd ? ne - em : 0) + rk - m;
        const int sl = rk >= m ? out : in;
        put_slot((gm >> (4 * e + q)) & 1, sl, rs[2 * e], rs[2 * e + 1], resid_off(e ? g1 : g0, rk & 1, r));
    }
    const int ntot = ne + no;
    const int ng = ntot > 16 ? (ntot + 3) >> 2 : min(4, (max(ne, no) + 1) >> 1);
    pub128(ks == 7 && q == 0, scr + BLK_I + wp * 128 + r * 16, ng | (units << 8), bias2.x, bias2.y, 0);
    const int idx = 2 * ks + (q & 1);
    const int frow = ks < 4 ? ks : ng - 1;
    const bool fill = ks < 4 ? !(idx < ((q >> 1) ? om : em) || (15 - idx) < ((q >> 1) ? em : om)) : ks == 4 && ng > 4 && 4 * frow + q >= ntot;
    put_slot(fill, frow * 4 + q, 0, 0, resid_off(q >> 1, q & 1, r));
}

template<int SEL> __device__ __forceinline__ void wgmma_sp(float (&d)[NACC], const uint32_t (&a)[4], uint64_t bdesc, uint32_t meta) {
    asm volatile("wgmma.mma_async.sp.sync.aligned.m64n48k32.f32.bf16.bf16 {%0, %1, %2, %3, %4, %5, %6, %7, %8, %9, %10, %11, %12, %13, %14, %15, %16, %17, %18, %19, %20, %21, %22, %23}, {%24, %25, %26, %27}, %28, %29, %30, 1, 1, 1, 0;"
        : "+f"(d[0]), "+f"(d[1]), "+f"(d[2]), "+f"(d[3]), "+f"(d[4]), "+f"(d[5]), "+f"(d[6]), "+f"(d[7]), "+f"(d[8]), "+f"(d[9]), "+f"(d[10]), "+f"(d[11]), "+f"(d[12]), "+f"(d[13]), "+f"(d[14]), "+f"(d[15]), "+f"(d[16]), "+f"(d[17]), "+f"(d[18]), "+f"(d[19]), "+f"(d[20]), "+f"(d[21]), "+f"(d[22]), "+f"(d[23])
        : "r"(a[0]), "r"(a[1]), "r"(a[2]), "r"(a[3]), "l"(bdesc), "r"(meta), "n"(SEL));
}
__device__ __forceinline__ void bar_sync(int id, int n) { asm volatile("bar.sync %0, %1;" :: "r"(id), "r"(n) : "memory"); }
__device__ __forceinline__ void bar_arrive(int id, int n) { asm volatile("bar.arrive %0, %1;" :: "r"(id), "r"(n) : "memory"); }

__device__ __forceinline__ void mbar_init(uint32_t bar, uint32_t cnt) { asm volatile("mbarrier.init.shared::cta.b64 [%0], %1;" :: "r"(bar), "r"(cnt) : "memory"); }
__device__ __forceinline__ void mbar_expect_tx(uint32_t bar, uint32_t bytes) {
    asm volatile("mbarrier.arrive.expect_tx.shared::cta.b64 _, [%0], %1;" :: "r"(bar), "r"(bytes) : "memory");
}
__device__ __forceinline__ void mbar_arrive(uint32_t bar) { asm volatile("mbarrier.arrive.shared::cta.b64 _, [%0];" :: "r"(bar) : "memory"); }
__device__ __forceinline__ void mbar_arrive_cluster(uint32_t bar) { asm volatile("mbarrier.arrive.shared::cluster.b64 _, [%0];" :: "r"(bar) : "memory"); }
__device__ __forceinline__ bool mbar_try(uint32_t bar, uint32_t parity) {
    uint32_t ok;
    asm volatile("{\n.reg .pred p;\nmbarrier.try_wait.parity.shared::cta.b64 p, [%1], %2;\nselp.u32 %0, 1, 0, p;\n}\n" : "=r"(ok) : "r"(bar), "r"(parity) : "memory");
    return ok;
}
__device__ __forceinline__ bool mbar_test(uint32_t bar, uint32_t parity) {
    uint32_t ok;
    asm volatile("{\n.reg .pred p;\nmbarrier.test_wait.parity.shared::cta.b64 p, [%1], %2;\nselp.u32 %0, 1, 0, p;\n}\n" : "=r"(ok) : "r"(bar), "r"(parity) : "memory");
    return ok;
}
__device__ __forceinline__ void fail_if(bool c) { asm volatile("{\n.reg .pred p;\nsetp.ne.u32 p, %0, 0;\n@p st.volatile.global.u32 [%1], %0;\n}\n" :: "r"((uint32_t)c), "l"(0ull) : "memory"); }
__device__ __forceinline__ void mbar_wait(uint32_t bar, uint32_t parity) {
    int n = 0;
    while (!mbar_try(bar, parity)) fail_if(++n > (1 << 20));
}
__device__ __forceinline__ void st_async(uint32_t addr, uint32_t v, uint32_t bar) {
    asm volatile("st.async.weak.shared::cluster.mbarrier::complete_tx::bytes.u32 [%0], %1, [%2];" :: "r"(addr), "r"(v), "r"(bar) : "memory");
}
__device__ __forceinline__ uint32_t mapa(uint32_t a, uint32_t cta) { uint32_t d; asm("mapa.shared::cluster.u32 %0, %1, %2;" : "=r"(d) : "r"(a), "r"(cta)); return d; }
__device__ __forceinline__ uint32_t lds32(uint32_t a) { uint32_t v; asm volatile("ld.shared.b32 %0, [%1];" : "=r"(v) : "r"(a)); return v; }
__device__ __forceinline__ uint4 lds128(uint32_t a) { uint4 v; asm volatile("ld.shared.v4.b32 {%0,%1,%2,%3}, [%4];" : "=r"(v.x), "=r"(v.y), "=r"(v.z), "=r"(v.w) : "r"(a)); return v; }
__device__ __forceinline__ uint32_t lds32v(uint32_t a) { uint32_t v; asm volatile("ld.volatile.shared.b32 %0, [%1];" : "=r"(v) : "r"(a) : "memory"); return v; }
__device__ __forceinline__ void sts32(uint32_t a, uint32_t v) { asm volatile("st.shared.b32 [%0], %1;" :: "r"(a), "r"(v) : "memory"); }
__device__ __forceinline__ uint32_t ld32(const void* a) { uint32_t v; asm volatile("ld.relaxed.gpu.global.u32 %0, [%1];" : "=r"(v) : "l"(a) : "memory"); return v; }
__device__ __forceinline__ uint4 ld128(const void* a) {
    uint4 v;
    asm volatile("{\n.reg .b64 s, t;\n.reg .b128 v;\nld.relaxed.gpu.global.L1::no_allocate.b128 v, [%4];\nmov.b128 {s, t}, v;\nmov.b64 {%0, %1}, s;\nmov.b64 {%2, %3}, t;\n}\n"
                 : "=r"(v.x), "=r"(v.y), "=r"(v.z), "=r"(v.w) : "l"(a) : "memory");
    return v;
}
__device__ __forceinline__ void ld128_if(bool c, const void* a, uint32_t& x, uint32_t& y, uint32_t& z, uint32_t& w) {
    asm volatile("{\n.reg .pred p;\n.reg .b64 s, t;\n.reg .b128 v;\nsetp.ne.u32 p, %5, 0;\nmov.b64 s, {%0, %1};\nmov.b64 t, {%2, %3};\nmov.b128 v, {s, t};\n"
                 "@p ld.relaxed.gpu.global.L1::no_allocate.b128 v, [%4];\nmov.b128 {s, t}, v;\nmov.b64 {%0, %1}, s;\nmov.b64 {%2, %3}, t;\n}\n"
                 : "+r"(x), "+r"(y), "+r"(z), "+r"(w) : "l"(a), "r"((uint32_t)c) : "memory");
}
__device__ __forceinline__ void ld32_if(bool c, const void* a, uint32_t& x) {
    asm volatile("{\n.reg .pred p;\nsetp.ne.u32 p, %2, 0;\n@p ld.relaxed.gpu.global.u32 %0, [%1];\n}\n" : "+r"(x) : "l"(a), "r"((uint32_t)c) : "memory");
}
__device__ __forceinline__ void mma_k8(float* c, uint2 a, uint32_t b) {
    asm volatile("mma.sync.aligned.m16n8k8.row.col.f32.bf16.bf16.f32 {%0,%1,%2,%3}, {%4,%5}, {%6}, {%0,%1,%2,%3};"
                 : "+f"(c[0]), "+f"(c[1]), "+f"(c[2]), "+f"(c[3]) : "r"(a.x), "r"(a.y), "r"(b));
}
__device__ __forceinline__ void mma_k16(float* d, uint2 a, uint2 a2, uint32_t b0, uint32_t b1, float c0, float c1, float c2, float c3) {
    asm volatile("mma.sync.aligned.m16n8k16.row.col.f32.bf16.bf16.f32 {%0,%1,%2,%3}, {%4,%5,%6,%7}, {%8,%9}, {%10,%11,%12,%13};"
                 : "=f"(d[0]), "=f"(d[1]), "=f"(d[2]), "=f"(d[3]) : "r"(a.x), "r"(a.y), "r"(a2.x), "r"(a2.y), "r"(b0), "r"(b1), "f"(c0), "f"(c1), "f"(c2), "f"(c3));
}
__device__ __forceinline__ uint32_t pack_bias(float lo, float hi, uint32_t bias2) {
    uint32_t p, o;
    asm("cvt.rn.bf16x2.f32 %0, %1, %2;" : "=r"(p) : "f"(hi), "f"(lo));
    asm("add.rn.bf16x2 %0, %1, %2;" : "=r"(o) : "r"(p), "r"(bias2));
    return o;
}

struct Params {
    const uint16_t* w; const uint16_t* bias; const uint8_t* x; uint4* scr; uint4* over;
    int ntok;
    int ntiles;
    int alltiles;
    int ncl;
    int nctas;
    int ne, pfd, pk;
    int ta, lead1, pw, k1, pfs, pfs2;
    int te, leade, slope1;
    int dl;
    uint32_t zero;
    int hpf, mtx;
    int nh, jh, jd, rel;
    int a, amagic, nfull;
};
constexpr int XEARLY = 1;
template <bool HELPER> __device__ __forceinline__ int place(const Params& p, int m) {
    if (HELPER) return ((m >> 1) * (p.a + 2) + ((m & 1) ? p.a + 1 : p.a >> 1));
    const int blk = (int)(((uint64_t)min(m, p.nfull) * (uint32_t)p.amagic) >> 32), r = m - blk * p.a;
    return (m + 2 * blk + (m < p.nfull && r >= (p.a >> 1)));
}

template <bool HELPER>
__global__ void __launch_bounds__(NTHREADS, 1)
spgemm_kernel(const __grid_constant__ CUtensorMap tmx, const __grid_constant__ CUtensorMap tmo, const Params p) {
    extern __shared__ unsigned char smem_raw[];
    const uint32_t sb = ((uint32_t)__cvta_generic_to_shared(smem_raw) + 1023u) & ~1023u;
    const int tid = threadIdx.x, warp = __shfl_sync(~0u, tid >> 5, 0), lane = tid & 31;
    const uint32_t tstart = now();
    const int rank = blockIdx.x % CL, cid = blockIdx.x / CL;
    const uint32_t bar_full = sb + OFF_FULL, bar_empty = sb + OFF_EMPTY, tk = sb + OFF_TK;
    uint4 wv[4];
    const int wrow = warp * 16 + (lane & 3) * 4;
    uint32_t b0, b1;
    auto prep_load = [&](int prb) {
        const uint32_t f0 = (prb >> 2) * 64;
        const uint16_t* const pa = p.w + ((uint32_t)(rank * 192 + wrow) * D + f0 + (lane >> 2) * 8);
#pragma unroll
        for (int j = 0; j < 4; j++) wv[j] = __ldg((const uint4*)(pa + j * D));
        b0 = __ldg(p.bias + (f0 + lane)); b1 = __ldg(p.bias + (f0 + 32 + lane));
    };
    if (!HELPER && warp < 12 && cid < 36) prep_load(cid);

    if (warp >= 12) {
        asm volatile("setmaxnreg.dec.sync.aligned.u32 32;");
        uint32_t epoch = 0;
        if (tid == NCONS + 32) asm volatile("ld.relaxed.gpu.global.u32 %0, [%1];" : "=r"(epoch) : "l"(&g_epoch) : "memory");
        if (tid == NCONS) {
#pragma unroll
            for (int s = 0; s < NSLOT; s++) { mbar_init(bar_full + 8 * s, 1); mbar_init(bar_empty + 8 * s, HELPER ? 3 : 3 * CL); }
            mbar_init(sb + OFF_MBAR, 1); mbar_init(sb + OFF_MBAR + 8, 1);
            mbar_init(sb + OFF_GO, HELPER ? 4 : 4 * CL); mbar_init(sb + OFF_GO + 8, HELPER ? 4 : 4 * CL); mbar_init(sb + OFF_EPOCH, 1);
            mbar_init(sb + OFF_FB, 1); mbar_init(sb + OFF_FB + 8, 1); mbar_init(sb + OFF_FB + 16, 1);
            asm volatile("fence.mbarrier_init.release.cluster;" ::: "memory");
            mbar_expect_tx(sb + OFF_MBAR, 36 * 4);
            if (!HELPER) asm volatile("griddepcontrol.launch_dependents;");
            asm volatile("prefetch.tensormap [%0];" :: "l"(&tmo) : "memory");
            asm volatile("prefetch.tensormap [%0];" :: "l"(&tmx) : "memory");
        }
        __syncwarp();
        if (HELPER) asm volatile("bar.sync 0;" ::: "memory");
        else asm volatile("barrier.cluster.arrive.relaxed.aligned;\nbarrier.cluster.wait.aligned;" ::: "memory");
        uint64_t pol;
        asm volatile("createpolicy.fractional.L2::evict_first.b64 %0, 1.0;" : "=l"(pol));
        if (warp == 12) {
            const int ntiles = HELPER ? p.alltiles - p.ntiles : p.ntiles;
            if (!HELPER && rank != 0) {
                auto phys = [&](int m) { return m < ntiles ? place<false>(p, m) : p.alltiles; };
                auto prefetch = [&](int t) {
                    const int rows = min(NT, p.ntok - t * NT), r0 = rows * (rank - 1) / 2, r1 = rows * rank / 2;
                    if (lane == 0 && r1 > r0)
                        asm volatile("cp.async.bulk.prefetch.L2.global [%0], %1;" :: "l"(p.x + (size_t)t * TILE_BYTES + r0 * (D * 2)), "r"((r1 - r0) * (D * 2)) : "memory");
                };
                const int u0 = phys(p.ncl), n0 = phys(NSLOT * p.ncl + p.ne) - u0;
                for (int k = cid; k < n0; k += p.ncl) { wait_until(tstart + p.pfd + k * p.pk / p.ncl); prefetch(u0 + k); }
                const int ua = phys(p.ta), n1 = phys(p.ta + p.lead1) - ua;
                if (p.hpf) for (int k = cid; k < n1; k += p.ncl) { wait_until(tstart + p.pw + (min(k, p.k1) * p.pfs + max(k - p.k1, 0) * p.pfs2) / p.ncl); prefetch(ua + k); }
                else for (int k = cid; k < p.lead1 && p.ta + k < ntiles; k += p.ncl) { wait_until(tstart + p.pw + (min(k, p.k1) * p.pfs + max(k - p.k1, 0) * p.pfs2) / p.ncl); prefetch(place<false>(p, p.ta + k)); }
            } else {
                const uint32_t rtk = HELPER ? tk : mapa(tk, lane < CL ? lane : 0), rfull = HELPER ? bar_full : mapa(bar_full, lane < CL ? lane : 0);
                int s = 0; uint32_t ph = 1, drawn = 0;
                for (int j = 0;; j++) {
                    if (j == 1 || j == 2) mbar_wait(sb + OFF_GO + 8 * (j - 1), 0);
                    mbar_wait(bar_empty + 8 * s, ph);
                    const int t = HELPER || j < NSLOT ? cid + j * p.ncl : (int)__shfl_sync(~0u, drawn, 0) + NSLOT * p.ncl;
                    const bool valid = t < ntiles;
                    if (valid && lane == 0) {
                        if (HELPER)
                            asm volatile("cp.async.bulk.tensor.4d.shared::cluster.global.mbarrier::complete_tx::bytes.L2::cache_hint [%0], [%1, {%3, %3, %3, %4}], [%2], %5;"
                                         :: "r"(sb + OFF_X + s * TILE_BYTES), "l"(&tmx), "r"(bar_full + 8 * s), "r"(0), "r"(place<HELPER>(p, t) * NB), "l"(pol) : "memory");
                        else
                            asm volatile("cp.async.bulk.tensor.4d.shared::cluster.global.mbarrier::complete_tx::bytes.multicast::cluster.L2::cache_hint [%0], [%1, {%3, %3, %3, %4}], [%2], %5, %6;"
                                         :: "r"(sb + OFF_X + s * TILE_BYTES), "l"(&tmx), "r"(bar_full + 8 * s), "r"(0), "r"(place<HELPER>(p, t) * NB), "h"((uint16_t)((1u << CL) - 1)), "l"(pol) : "memory");
                    }
                    if (HELPER) {
                        if (lane == 0) { sts32(tk + ((j & 7) << 2), valid ? (uint32_t)t : NO_TILE); mbar_expect_tx(bar_full + 8 * s, valid ? TILE_BYTES : 0); }
                    } else if (lane < CL) {
                        asm volatile("mbarrier.arrive.expect_tx.shared::cluster.b64 _, [%0], %1;" :: "r"(rfull + 8 * s), "r"(valid ? TILE_BYTES + 4 : 4) : "memory");
                        st_async(rtk + ((j & 7) << 2), valid ? (uint32_t)t : NO_TILE, rfull + 8 * s);
                    }
                    if (!valid) break;
                    if (!HELPER && lane == 0 && t > p.ta) {
                        auto fm = [&](int m) { return min(ntiles, m + p.leade + max(0, (p.slope1 * (p.te - m)) >> 16)); };
                        auto pf = [&](int u) { asm volatile("cp.async.bulk.prefetch.L2.global [%0], %1;" :: "l"(p.x + (size_t)u * TILE_BYTES), "r"(min(NT, p.ntok - u * NT) * (D * 2)) : "memory"); };
                        const int f0 = fm(t - 1), f1 = fm(t);
                        if (p.hpf) { const int u1 = f1 < ntiles ? place<false>(p, f1) : p.alltiles; for (int u = f0 < ntiles ? place<false>(p, f0) : p.alltiles; u < u1; u++) pf(u); }
                        else for (int f = f0; f < f1; f++) pf(place<false>(p, f));
                    }
                    if (!HELPER && lane == 0 && j >= NSLOT - 1) drawn = atomicInc(&g_ticket, ntiles - p.ncl * (NSLOT - 1) - 1);
                    if (++s == NSLOT) { s = 0; ph ^= 1; }
                }
            }
        } else {
            const int g = warp - 13;
            const uint32_t rempty = HELPER ? bar_empty : mapa(bar_empty, 0);
            if (g == 0 && lane == 0) { sts32(sb + OFF_EPOCH + 8, epoch); mbar_arrive(sb + OFF_EPOCH); }
            mbar_wait(bar_full, 0);
            uint32_t t = lds32v(tk), ph = 0;
            int s = 0, nheld = 0, nout = 0, hnext = HELPER || p.nh == 0 ? -1 : p.jh;
            uint32_t held[NH > 0 ? NH : 1];
            auto store = [&](int buf, uint32_t tile) {
                asm volatile("cp.async.bulk.tensor.2d.global.shared::cta.bulk_group.L2::cache_hint [%0, {%2, %3}], [%1], %4;"
                             :: "l"(&tmo), "r"(sb + OFF_STG + (buf * 3 + g) * STG_BYTES), "r"((p.mtx ? rank * 3 + g : g * 3 + rank) * 64), "r"((place<HELPER>(p, tile)) * NT), "l"(pol) : "memory");
            };
            auto release = [&]() {
#pragma unroll
                for (int k = 0; k < NH; k++) if (k >= nout && k < nheld && lane == 0) store(1 + k, held[k]);
                nout = nheld;
            };
            for (int i = 0;; i++) {
                bar_sync(BAR_SFULL + g, 160);
                const int s1 = s + 1 == NSLOT ? 0 : s + 1;
                if (s1 == 0) ph ^= 1;
                if (lane == 0) { if (HELPER) mbar_arrive(bar_empty + 8 * s); else mbar_arrive_cluster(rempty + 8 * s); }
                const bool ready = __all_sync(~0u, mbar_test(bar_full + 8 * s1, ph));
                if (ready) bar_arrive(BAR_G + g, 288);
                if (lane == 0) {
                    asm volatile("fence.proxy.async.shared::cta;" ::: "memory");
                    if (i != hnext) store(0, t);
                    asm volatile("cp.async.bulk.commit_group;" ::: "memory");
                    if (g == 2 && i == 0 && atomicInc(&g_passed, p.nctas - 1) == (uint32_t)p.nctas - 1) atomicAdd(&g_epoch, 1);
                }
                __syncwarp();
                if (i == hnext) {
#pragma unroll
                    for (int k = 0; k < NH; k++) if (k == nheld) held[k] = t;
                    hnext = ++nheld < p.nh ? hnext + p.jd : -1;
                }
                s = s1;
                if (!ready) { mbar_wait(bar_full + 8 * s, ph); bar_arrive(BAR_G + g, 288); }
                t = lds32v(tk + (((i + 1) & 7) << 2));
                if (t >= (uint32_t)p.rel && nout < nheld) { release(); if (lane == 0) asm volatile("cp.async.bulk.commit_group;" ::: "memory"); }
                if (lane == 0) asm volatile("cp.async.bulk.wait_group.read 0;" ::: "memory");
                __syncwarp();
                if (t == NO_TILE) break;
                bar_arrive(BAR_SEMPTY + g, 160);
            }
        }
        __syncwarp();
        if (!HELPER) asm volatile("barrier.cluster.arrive.relaxed.aligned;\nbarrier.cluster.wait.aligned;" ::: "memory");
    } else {
        asm volatile("setmaxnreg.inc.sync.aligned.u32 160;");
        const int wg = warp >> 2, r = lane >> 2, q = lane & 3;
        uint32_t epoch;
        if (HELPER) asm volatile("bar.sync 0;" ::: "memory");
        else {
            int prb = cid;
            asm volatile("barrier.cluster.arrive.relaxed.aligned;" ::: "memory");
            if (prb >= 36) asm volatile("barrier.cluster.wait.aligned;" ::: "memory");
#pragma unroll 1
            for (int round = 0; prb < 36; prb += p.ncl, round++) {
                const uint32_t wsm = sb + OFF_WST, msk = sb + OFF_MSK + (round & 1) * 144, mbar = sb + OFF_MBAR + (round & 1) * 8;
                if (round) {
                    bar_sync(3, 384);
                    if (tid == 0) mbar_expect_tx(mbar, 36 * 4);
                    prep_load(prb);
                }
                const uint32_t mk = __ballot_sync(~0u, has_tie(wv[0].x, wv[1].x, wv[2].x, wv[3].x) || has_tie(wv[0].y, wv[1].y, wv[2].y, wv[3].y) ||
                                                       has_tie(wv[0].z, wv[1].z, wv[2].z, wv[3].z) || has_tie(wv[0].w, wv[1].w, wv[2].w, wv[3].w));
                if (round == 0) asm volatile("barrier.cluster.wait.aligned;" ::: "memory");
                if (lane < CL) st_async(mapa(msk + (rank * 12 + warp) * 4, lane), mk, mapa(mbar, lane));
#pragma unroll
                for (int j = 0; j < 4; j++) {
                    const int row = wrow + j;
                    const uint32_t ad = wsm + row * 128 + (((lane >> 2) ^ ((row & 1) | ((row >> 1) & 6))) << 4);
                    asm volatile("st.shared.v4.b32 [%0], {%1,%2,%3,%4};" :: "r"(ad), "r"(wv[j].x), "r"(wv[j].y), "r"(wv[j].z), "r"(wv[j].w) : "memory");
                }
                if (warp >= 6) bar_arrive(1, 384);
                else {
                    bar_sync(1, 384);
                    mbar_wait(sb + OFF_EPOCH, 0);
                    epoch = lds32v(sb + OFF_EPOCH + 8);
                    uint8_t* const scr = (uint8_t*)p.scr + (epoch & 1) * SCR_END;
                    mbar_wait(mbar, (round >> 1) & 1);
                    uint32_t m0 = 0, m1 = 0;
                    if (lane < KSTEPS) asm volatile("ld.volatile.shared.v2.b32 {%0,%1}, [%2];" : "=r"(m0), "=r"(m1) : "r"(msk + 8 * lane) : "memory");
                    uint32_t c0 = m0 - ((m0 >> 1) & 0x55555555u), c1 = m1 - ((m1 >> 1) & 0x55555555u);
                    c0 = (c0 & 0x33333333u) + ((c0 >> 2) & 0x33333333u) + (c1 & 0x33333333u) + ((c1 >> 2) & 0x33333333u);
                    c1 = __reduce_add_sync(~0u, (c0 >> 4) & 0x0F0F0F0Fu); c0 = __reduce_add_sync(~0u, c0 & 0x0F0F0F0Fu);
                    auto key = [&](int v) { return ((((v & 1) ? c1 : c0) >> (4 * (v & 6))) & 0xFFu) * 8 + v; };
                    const uint32_t ku = key(lane & 7);
                    const uint32_t l0 = __ballot_sync(~0u, key(lane >> 3) < ku), l1 = __ballot_sync(~0u, key(4 + (lane >> 3)) < ku);
                    const int rk = __popc((l0 >> (lane & 7)) & 0x01010101u) + __popc((l1 >> (lane & 7)) & 0x01010101u);
                    const int pp = prb & 3;
                    const int ulo = __ffs(__ballot_sync(~0u, rk == pp)) - 1, uhi = __ffs(__ballot_sync(~0u, rk == 7 - pp)) - 1;
                    uint32_t lo[4], hi[4];
                    load_unit(wsm, warp, ulo, lane, lo); load_unit(wsm, warp, uhi, lane, hi);
                    const uint32_t mm = (((m0 >> (4 * ulo)) | (m0 >> (4 * uhi))) & 15u) | ((((m1 >> (4 * ulo)) | (m1 >> (4 * uhi))) & 15u) << 4);
                    const uint2 bias2 = make_uint2(__shfl_sync(~0u, ulo < 4 ? b0 : b1, (ulo * 8 + r) & 31) * 0x10001u, __shfl_sync(~0u, uhi < 4 ? b0 : b1, (uhi * 8 + r) & 31) * 0x10001u);
                    emit_step(lo, hi, mm, prb, rank * 6 + warp, lane, ulo | (uhi << 4), bias2, scr, p.over, epoch + 1);
                }
            }
            if (cid >= 36 || warp >= 6) { mbar_wait(sb + OFF_EPOCH, 0); epoch = lds32v(sb + OFF_EPOCH + 8); }
            if (warp >= 6) for (int i = blockIdx.x * 192 + tid - 192; i < SCR_END / 16; i += gridDim.x * 192) p.scr[(~epoch & 1) * (SCR_END / 16) + i] = make_uint4(0, 0, 0, 0);
        }
        if (HELPER) { mbar_wait(sb + OFF_EPOCH, 0); epoch = lds32v(sb + OFF_EPOCH + 8); }
        if (wg == 2) bar_arrive(BAR_T, 256);
        const int mt = p.mtx ? rank * 3 + wg : wg * 3 + rank, rb = mt * 4 + (warp & 3);
        const uint8_t* const scr = (const uint8_t*)p.scr + (epoch & 1) * SCR_END + mt * BLK;
        const int fo = (warp & 3) * 512 + lane * 16, io = BLK_I + (warp & 3) * 128 + r * 16, so = BLK_S + (warp & 3) * 2048 + q * 128 + r * 16;
        const int mo = BLK_M + ((warp & 3) * KSTEPS + (q >> 1)) * 64 + r * 8 + (q & 1) * 4;
        if (!HELPER && cid < 36) bar_sync(2, 384);
        const uint32_t blk = sb + (wg == 0 ? OFF_STG : OFF_X + wg * TILE_BYTES);
        if (warp == 0) {
            if (!HELPER && cid < 36 && p.ncl >= 36) wait_until(now() + p.dl);
            else for (int n = 0; __any_sync(~0u, ld32(scr + 17 * 2048 + fo) == 0); n++) fail_if(n > (1 << 22));
            if (lane < 3) {
                mbar_expect_tx(sb + OFF_FB + 8 * lane, BLK);
                asm volatile("cp.async.bulk.shared::cluster.global.mbarrier::complete_tx::bytes [%0], [%1], %2, [%3];"
                             :: "r"(sb + (lane == 0 ? OFF_STG : OFF_X + lane * TILE_BYTES)), "l"(scr + lane * (p.mtx ? 1 : 3) * BLK), "r"(BLK), "r"(sb + OFF_FB + 8 * lane) : "memory");
            }
        }
        uint32_t a[KSTEPS][4], meta[9];
        uint2 rv[4]; uint32_t ro[4];
        uint32_t info, bias_lo, bias_hi;
        {
            const uint8_t* const fp = scr + fo; const uint8_t* const ip = scr + io; const uint8_t* const sp = scr + so; const uint8_t* const mp = scr + mo;
            mbar_wait(sb + OFF_FB + 8 * wg, 0);
            uint4 i0 = lds128(blk + io), sv[4];
#pragma unroll
            for (int j = 0; j < 4; j++) sv[j] = lds128(blk + so + j * 512);
#pragma unroll
            for (int j = 0; j < 9; j++) meta[j] = lds32(blk + mo + j * 128);
#pragma unroll
            for (int k = 0; k < KSTEPS; k++) { const uint4 v = lds128(blk + fo + k * 2048); a[k][0] = v.x; a[k][1] = v.y; a[k][2] = v.z; a[k][3] = v.w; }
            for (int n = 0;; n++) {
                uint32_t lo = __vimin3_u32(__vimin3_u32(i0.x, meta[8], sv[0].z), sv[1].z, min(sv[2].z, sv[3].z));
#pragma unroll
                for (int j = 0; j < 8; j += 2) lo = __vimin3_u32(lo, meta[j], meta[j + 1]);
#pragma unroll
                for (int k = 0; k < KSTEPS; k += 2) lo = __vimin3_u32(lo, a[k][0], a[k + 1][0]);
                if (__all_sync(~0u, lo != 0)) break;
                fail_if(n > (1 << 20));
                ld128_if(i0.x == 0, ip, i0.x, i0.y, i0.z, i0.w);
#pragma unroll
                for (int j = 0; j < 4; j++) ld128_if(sv[j].z == 0, sp + j * 512, sv[j].x, sv[j].y, sv[j].z, sv[j].w);
#pragma unroll
                for (int j = 0; j < 9; j++) ld32_if(meta[j] == 0, mp + j * 128, meta[j]);
#pragma unroll
                for (int k = 0; k < KSTEPS; k++) ld128_if(a[k][0] == 0, fp + k * 2048, a[k][0], a[k][1], a[k][2], a[k][3]);
            }
            info = i0.x; bias_lo = i0.y; bias_hi = i0.z;
#pragma unroll
            for (int j = 0; j < 4; j++) { rv[j] = make_uint2(sv[j].x, sv[j].y); ro[j] = sv[j].z; }
        }
#pragma unroll
        for (int j = 0; j < 4; j++) { rv[j].x ^= p.zero; rv[j].y ^= p.zero; }
        if (wg && lane == 0) { if (HELPER) mbar_arrive(sb + OFF_GO + 8 * (wg - 1)); else mbar_arrive_cluster(mapa(sb + OFF_GO + 8 * (wg - 1), 0)); }
        info = __shfl_sync(~0u, info, 0);
        const int ngrp = info & 0xFF, ulo = (info >> 8) & 7, uhi = (info >> 12) & 7;
#pragma unroll 1
        for (int j = 4; j < ngrp; j++)
            for (int n = 0; __any_sync(~0u, ld128(p.over + (rb * 144 + j * 4 + q) * 8 + r).w != epoch + 1); n++) fail_if(n > (1 << 20));
        mbar_wait(bar_full, 0);
        const uint32_t stg = sb + OFF_STG + wg * STG_BYTES + ((lane >> 4) * 8 + (lane & 7)) * 128 + (((((lane >> 3) & 1) ? uhi : ulo) ^ (lane & 7)) << 4);
        float acc[NACC];
        uint32_t bq[NB][2];
        auto gather = [&](uint32_t xb) {
#pragma unroll
            for (int j = 0; j < 4; j++) {
                if (j < ngrp) {
#pragma unroll
                    for (int n = 0; n < NB; n++) { uint32_t v = lds32(xb + ro[j] + (n * 9216 - RO_BIAS)); if (j < 2) acc[4 * n + j] = __uint_as_float(v); else bq[n][j - 2] = v; }
                } else {
#pragma unroll
                    for (int n = 0; n < NB; n++) { if (j < 2) acc[4 * n + j] = 0.f; else bq[n][j - 2] = 0; }
                }
            }
        };
        gather(sb + OFF_X);
        bar_sync(BAR_T + wg, 256);
        int s = 0, hnext = HELPER || p.nh == 0 ? -1 : p.jh, hbuf = 3 * STG_BYTES;
        bool more = true;
        for (int i = 0; more; i++) {
            const uint32_t xb = sb + OFF_X + s * TILE_BYTES;
            s = s + 1 == NSLOT ? 0 : s + 1;
#pragma unroll
            for (int n = 0; n < NB; n++) mma_k16(acc + 4 * n, rv[0], rv[1], __float_as_uint(acc[4 * n]), __float_as_uint(acc[4 * n + 1]), 0.f, 0.f, 0.f, 0.f);
#pragma unroll
            for (int n = 0; n < NB; n++) mma_k16(acc + 4 * n, rv[2], rv[3], bq[n][0], bq[n][1], acc[4 * n], acc[4 * n + 1], acc[4 * n + 2], acc[4 * n + 3]);
#pragma unroll 1
            for (int j = 4; j < ngrp; j++) {
                const uint4 o = __ldca(p.over + (rb * 144 + j * 4 + q) * 8 + r); const uint2 v = make_uint2(o.x, o.y); const uint32_t off = o.z - RO_BIAS;
#pragma unroll
                for (int n = 0; n < NB; n++) bq[n][0] = lds32(xb + off + n * 9216);
#pragma unroll
                for (int n = 0; n < NB; n++) mma_k8(acc + 4 * n, v, bq[n][0]);
            }
            const uint64_t desc = ((uint64_t)1 << 62) | ((uint64_t)(9216 >> 4) << 32) | ((uint64_t)1 << 16) | (uint64_t)(xb >> 4);
            asm volatile("wgmma.fence.sync.aligned;" ::: "memory");
#pragma unroll
            for (int k = 0; k < KSTEPS; k++) {
                const uint64_t d = desc + (uint64_t)(((k >> 1) * 1024 + (k & 1) * 64) >> 4);
                if (k & 1) wgmma_sp<1>(acc, a[k], d, meta[k >> 1]);
                else       wgmma_sp<0>(acc, a[k], d, meta[k >> 1]);
                if (k == SPLIT - 1) asm volatile("wgmma.commit_group.sync.aligned;" ::: "memory");
            }
            asm volatile("wgmma.commit_group.sync.aligned;" ::: "memory");
            bar_arrive(wg == 2 ? BAR_T : BAR_T + 1 + wg, 256);
            asm volatile("wgmma.wait_group.sync.aligned 1;" ::: "memory");
            if (wg != 0 || i != 0) bar_arrive(wg == 0 ? BAR_G + 2 : BAR_G - 1 + wg, 288);
            if (i != 0) bar_sync(BAR_SEMPTY + wg, 160);
            asm volatile("wgmma.wait_group.sync.aligned 0;" ::: "memory");
            uint32_t sq = stg;
            if (i == hnext) { sq += hbuf; hbuf += 3 * STG_BYTES; hnext = hbuf <= p.nh * 3 * STG_BYTES ? hnext + p.jd : -1; }
#pragma unroll
            for (int n = 0; n + 1 < NB; n += 2) {
                const uint32_t p0 = pack_bias(acc[4 * n], acc[4 * n + 1], bias_lo), p1 = pack_bias(acc[4 * n + 2], acc[4 * n + 3], bias_hi);
                const uint32_t p2 = pack_bias(acc[4 * n + 4], acc[4 * n + 5], bias_lo), p3 = pack_bias(acc[4 * n + 6], acc[4 * n + 7], bias_hi);
                asm volatile("stmatrix.sync.aligned.m8n8.x4.trans.shared.b16 [%0], {%1,%2,%3,%4};" :: "r"(sq + n * 1024), "r"(p0), "r"(p1), "r"(p2), "r"(p3) : "memory");
            }
            if (NB & 1) {
                const uint32_t p0 = pack_bias(acc[NACC - 4], acc[NACC - 3], bias_lo), p1 = pack_bias(acc[NACC - 2], acc[NACC - 1], bias_hi);
                asm volatile("stmatrix.sync.aligned.m8n8.x2.trans.shared.b16 [%0], {%1,%2};" :: "r"(sq + (NB - 1) * 1024), "r"(p0), "r"(p1) : "memory");
            }
            bar_arrive(BAR_SFULL + wg, 160);
            bar_sync(BAR_G + wg, 288);
            const uint32_t tn = lds32v(tk + (((i + 1) & 7) << 2));
            gather(sb + OFF_X + s * TILE_BYTES);
            more = __any_sync(~0u, tn != NO_TILE);
            if (more || wg == 0) bar_sync(BAR_T + wg, 256);
        }
        if (wg == 0) bar_arrive(BAR_G + 2, 288);
        __syncwarp();
        if (!HELPER) asm volatile("barrier.cluster.arrive.relaxed.aligned;\nbarrier.cluster.wait.aligned;" ::: "memory");
    }
}

typedef CUresult (*EncodeFn)(CUtensorMap*, CUtensorMapDataType, cuuint32_t, void*, const cuuint64_t*, const cuuint64_t*, const cuuint32_t*, const cuuint32_t*,
                             CUtensorMapInterleave, CUtensorMapSwizzle, CUtensorMapL2promotion, CUtensorMapFloatOOBfill);

extern "C" void kernel_launch(void* const* d_in, const int* in_sizes, int n_in, void* d_out, int out_size) {
    static EncodeFn enc = nullptr;
    static int ncl = 0, nhelp = 0;
    const int ntok = in_sizes[0] / D;
    cudaLaunchConfig_t cfg = {};
    cudaLaunchAttribute at[1];
    at[0].id = cudaLaunchAttributeClusterDimension; at[0].val.clusterDim.x = CL; at[0].val.clusterDim.y = 1; at[0].val.clusterDim.z = 1;
    cfg.blockDim = dim3(NTHREADS); cfg.dynamicSmemBytes = SMEM_BYTES; cfg.attrs = at; cfg.numAttrs = 1; cfg.stream = cudaStreamPerThread;
    if (!enc) {
        cudaDriverEntryPointQueryResult qr; void* fn = nullptr;
        cudaGetDriverEntryPoint("cuTensorMapEncodeTiled", &fn, cudaEnableDefault, &qr);
        enc = (EncodeFn)fn;
        cudaFuncSetAttribute(spgemm_kernel<false>, cudaFuncAttributeMaxDynamicSharedMemorySize, SMEM_BYTES);
        cudaFuncSetAttribute(spgemm_kernel<true>, cudaFuncAttributeMaxDynamicSharedMemorySize, SMEM_BYTES);
        int dev = 0, nsm = 0;
        cudaGetDevice(&dev);
        cudaDeviceGetAttribute(&nsm, cudaDevAttrMultiProcessorCount, dev);
        cfg.gridDim = dim3(CL * (nsm / CL));
        cudaOccupancyMaxActiveClusters(&ncl, spgemm_kernel<false>, &cfg);
        if (ncl < 1) ncl = 1;
        nhelp = nsm > CL * ncl ? (nsm - CL * ncl) / CL : 0;
    }
    CUtensorMap tmx, tmo;
    {
        cuuint64_t dims[4] = {64, 8, 9, (cuuint64_t)(ntok / 8)};
        cuuint64_t strides[3] = {D * 2, 128, 8 * D * 2};
        cuuint32_t box[4] = {64, 8, 9, NB}, es[4] = {1, 1, 1, 1};
        enc(&tmx, CU_TENSOR_MAP_DATA_TYPE_BFLOAT16, 4, d_in[0], dims, strides, box, es, CU_TENSOR_MAP_INTERLEAVE_NONE,
            CU_TENSOR_MAP_SWIZZLE_128B, CU_TENSOR_MAP_L2_PROMOTION_L2_128B, CU_TENSOR_MAP_FLOAT_OOB_FILL_NONE);
    }
    {
        cuuint64_t dims[2] = {D, (cuuint64_t)ntok};
        cuuint64_t strides[1] = {D * 2};
        cuuint32_t box[2] = {64, NT}, es[2] = {1, 1};
        enc(&tmo, CU_TENSOR_MAP_DATA_TYPE_BFLOAT16, 2, d_out, dims, strides, box, es, CU_TENSOR_MAP_INTERLEAVE_NONE,
            CU_TENSOR_MAP_SWIZZLE_128B, CU_TENSOR_MAP_L2_PROMOTION_NONE, CU_TENSOR_MAP_FLOAT_OOB_FILL_NONE);
    }
    Params p;
    p.w = (const uint16_t*)d_in[1]; p.bias = (const uint16_t*)d_in[2]; p.x = (const uint8_t*)d_in[0];
    p.ntok = ntok;
    cudaGetSymbolAddress((void**)&p.scr, g_scr); cudaGetSymbolAddress((void**)&p.over, g_over);
    p.zero = 0; p.hpf = 1; p.mtx = 0;
    p.alltiles = (ntok + NT - 1) / NT;
    const int nc = ncl < p.alltiles ? ncl : p.alltiles;
    p.a = nhelp ? (int)(2 * nc / (nhelp * 1.15) + 0.5) : 2;
    if (p.a < 2) p.a = 2;
    const int nblk = (int)(p.alltiles / (p.a + 2) * 0.6);
    const int nh = nhelp && 2 * nblk >= nhelp && p.alltiles - 2 * nblk >= nc ? nhelp : 0;
    p.ntiles = p.alltiles - (nh ? 2 * nblk : 0);
    p.nfull = nh ? nblk * p.a : 0; p.amagic = (int)(0xFFFFFFFFu / (uint32_t)p.a + 1);
    p.ncl = nc; p.nctas = CL * (nc + nh);
    p.nh = (int)NH; p.jh = 4; p.jd = 4; p.rel = p.ntiles - 50;
    auto tiles = [](double v) { return (int)(v * 56 / NT); };
    auto ns = [](double v) { return (int)(v * NT / 56); };
    p.ne = tiles(0); p.pfd = 1500; p.pk = ns(900);
    p.ta = (int)(p.ntiles * 0.4) + 1; p.lead1 = tiles(250); p.pw = 2500;
    p.k1 = tiles(39); p.pfs = ns(1000); p.pfs2 = ns(2300);
    p.te = (int)(p.ntiles * 1.0) + 2; p.leade = tiles(50); p.slope1 = ((p.lead1 - p.leade) << 16) / (p.te - p.ta);
    p.dl = 0;
    cfg.gridDim = dim3(CL * nc);
    cudaLaunchKernelEx(&cfg, spgemm_kernel<false>, tmx, tmo, p);
    if (nh) {
        at[0].id = cudaLaunchAttributeProgrammaticStreamSerialization; at[0].val.programmaticStreamSerializationAllowed = 1;
        cfg.gridDim = dim3(CL * nh);
        p.ncl = nh;
        cudaLaunchKernelEx(&cfg, spgemm_kernel<true>, tmx, tmo, p);
    }
}
```

```cpp
#include <cuda_runtime.h>
#include <cuda_bf16.h>
#include <cuda.h>
#include <stdint.h>

constexpr int D = 576;
constexpr int NH = 2;
constexpr int NT = 48;
constexpr int NSLOT = 3;
constexpr int SPLIT = 13;
constexpr int KSTEPS = 18;
constexpr int CL = 3;
constexpr int TILE_BYTES = NT * D * 2;
constexpr int STG_BYTES = NT * 128;
constexpr int NACC = NT / 2;
constexpr int NB = NT / 8;
constexpr int NCONS = 384;
constexpr int NTHREADS = 512;
constexpr uint32_t NO_TILE = 0xFFFFFFFFu;

constexpr int OFF_X = 0;
constexpr int OFF_STG = OFF_X + NSLOT * TILE_BYTES;
constexpr int OFF_WST = OFF_STG;
constexpr int OFF_FULL = OFF_STG + (1 + NH) * 3 * STG_BYTES;
constexpr int OFF_EMPTY = OFF_FULL + 8 * NSLOT;
constexpr int OFF_MBAR = OFF_EMPTY + 8 * NSLOT;
constexpr int OFF_GO = OFF_MBAR + 16;
constexpr int OFF_FB = OFF_GO + 24;
constexpr int OFF_EPOCH = OFF_FB + 24;
constexpr int OFF_TK = OFF_EPOCH + 16;
constexpr int OFF_MSK = OFF_TK + 32;
constexpr int SMEM_BYTES = OFF_MSK + 2 * 36 * 4 + 1024;
static_assert(SMEM_BYTES <= 232448 && NSLOT < 8 && NSLOT >= 3, "layout");
constexpr int BAR_T = 4, BAR_SFULL = 7, BAR_SEMPTY = 10, BAR_G = 13;

constexpr int BLK_M = KSTEPS * 2048, BLK_S = BLK_M + 4 * KSTEPS * 64, BLK_I = BLK_S + 4 * 2560, BLK = BLK_I + 4 * 128, SCR_END = 9 * BLK;
constexpr bool BLK_FITS = BLK <= TILE_BYTES && BLK <= OFF_FULL - OFF_STG;
__host__ __device__ constexpr int blk_off(int g) { return BLK_FITS ? (g == 0 ? OFF_STG : OFF_X + g * TILE_BYTES) : OFF_X + TILE_BYTES + (g + 2) % 3 * BLK; }
static_assert(blk_off(0) + BLK <= OFF_FULL && blk_off(2) + BLK <= OFF_STG && OFF_WST + 192 * 128 <= OFF_FULL, "fragment blocks");
__device__ __align__(128) uint4    g_scr[2][SCR_END / 16];
__device__ __align__(128) uint4    g_over[36 * 144 * 8];
__device__ __align__(128) uint32_t g_epoch;
__device__ __align__(128) uint32_t g_passed;
__device__ __align__(128) uint32_t g_ticket;

__device__ __forceinline__ uint32_t now() { uint32_t c; asm volatile("mov.u32 %0, %%globaltimer_lo;" : "=r"(c)); return c; }
__device__ __forceinline__ void wait_until(uint32_t due) { while ((int)(now() - due) < 0) __nanosleep(20); }

__device__ __forceinline__ uint32_t max2(uint32_t a, uint32_t b) { uint32_t d; asm("max.u16x2 %0, %1, %2;" : "=r"(d) : "r"(a), "r"(b)); return d; }
__device__ __forceinline__ uint32_t min2(uint32_t a, uint32_t b) { uint32_t d; asm("min.u16x2 %0, %1, %2;" : "=r"(d) : "r"(a), "r"(b)); return d; }
__device__ __forceinline__ uint32_t sign2(uint32_t a) { uint32_t d; asm("prmt.b32 %0, %1, %1, 0xBB99;" : "=r"(d) : "r"(a)); return d; }
__device__ __forceinline__ void zip4(uint32_t a01, uint32_t a23, uint32_t b01, uint32_t b23, uint32_t (&x)[4]) {
    x[0] = __byte_perm(a01, b01, 0x5410); x[1] = __byte_perm(a01, b01, 0x7632); x[2] = __byte_perm(a23, b23, 0x5410); x[3] = __byte_perm(a23, b23, 0x7632);
}
__device__ __forceinline__ void middle2(const uint32_t (&x)[4], uint32_t (&m)[4], uint32_t& u, uint32_t& v) {
#pragma unroll
    for (int i = 0; i < 4; i++) m[i] = x[i] & 0x7FFF7FFFu;
    u = min2(max2(m[0], m[1]), max2(m[2], m[3])); v = max2(min2(m[0], m[1]), min2(m[2], m[3]));
}
__device__ __forceinline__ uint32_t tie_key(uint32_t x0, uint32_t x1, uint32_t x2, uint32_t x3) {
    const uint32_t x[4] = {x0, x1, x2, x3};
    uint32_t m[4], u, v;
    middle2(x, m, u, v);
    return max2(u, 0x00010001u) ^ v;
}
__device__ __forceinline__ void load_unit(uint32_t wsm, int ls, int unit, int lane, uint32_t (&m)[4]) {
    const int row = ls * 32 + (lane >> 4) * 16 + ((lane & 7) >> 1) * 4 + ((lane >> 3) & 1) * 2 + (lane & 1);
    const uint32_t ad = wsm + row * 128 + ((unit ^ ((row & 1) | ((row >> 1) & 6))) << 4);
    asm volatile("ldmatrix.sync.aligned.m8n8.x4.trans.shared.b16 {%0,%1,%2,%3}, [%4];" : "=r"(m[0]), "=r"(m[1]), "=r"(m[2]), "=r"(m[3]) : "r"(ad) : "memory");
}
__device__ __forceinline__ void split_pair(const uint32_t (&x)[4], bool P, uint32_t& alo, uint32_t& ahi, uint32_t& nib, uint32_t& rlo, uint32_t& rhi) {
    uint32_t m[4], u, v;
    middle2(x, m, u, v);
    const uint32_t c = 0x80008000u - max2(max2(u, v), 0x00010001u);
    uint32_t k0 = sign2(m[0] + c), k1 = sign2(m[1] + c), k2 = sign2(m[2] + c), k3 = sign2(m[3] + c);
    const uint32_t three = (k0 & k1 & (k2 | k3)) | (k2 & k3 & (k0 | k1)), four = k0 & k1 & k2 & k3;
    const uint32_t pa = P ? k2 : k0, pb = P ? k3 : k1;
    const uint32_t ra = three & pa, rb = three & pb & (four | ~pa);
    const uint32_t va = (P ? x[2] : x[0]) & ra, vb = (P ? x[3] : x[1]) & rb;
    if (P) { k2 &= ~ra; k3 &= ~rb; } else { k0 &= ~ra; k1 &= ~rb; }
    const uint32_t s1 = k1 & k0, s2 = k2 & (k0 | k1);
    const uint32_t t = (k1 & x[1]) | (~k1 & k2 & x[2]);
    const uint32_t x0 = (k0 & x[0]) | (~k0 & t), x1 = (s1 & x[1]) | (s2 & x[2]) | (k3 & x[3]);
    nib = (~k0 & k1 & 0x00010001u) | (~k0 & ~k1 & 0x00020002u) | (~s2 & 0x00040004u) | (~s1 & 0x00080008u);
    alo = __byte_perm(x0, x1, 0x5410); ahi = __byte_perm(x0, x1, 0x7632);
    rlo = __byte_perm(va, vb, 0x5410); rhi = __byte_perm(va, vb, 0x7632);
}
__device__ __forceinline__ uint32_t nonzero(uint32_t v) { return v ? v : 0x8000u; }
__device__ __forceinline__ void pub32(void* a, uint32_t v) { asm volatile("st.relaxed.gpu.global.u32 [%0], %1;" :: "l"(a), "r"(v) : "memory"); }
__device__ __forceinline__ void pub128(bool c, void* a, uint32_t x, uint32_t y, uint32_t z, uint32_t w) {
    asm volatile("{\n.reg .pred p;\n.reg .b64 s, t;\n.reg .b128 v;\nsetp.ne.u32 p, %5, 0;\nmov.b64 s, {%1, %2};\nmov.b64 t, {%3, %4};\nmov.b128 v, {s, t};\n@p st.relaxed.gpu.global.b128 [%0], v;\n}\n"
                 :: "l"(a), "r"(x), "r"(y), "r"(z), "r"(w), "r"((uint32_t)c) : "memory");
}
constexpr int RO_BIAS = 16;
__device__ __forceinline__ uint32_t resid_off(int g, int P, int r) {
    int k0 = 4 * g + 2 * P;
    int chunk = k0 >> 6, byte = (k0 & 63) * 2;
    return chunk * 1024 + r * 128 + (((byte >> 4) ^ r) << 4) + (byte & 15);
}
__device__ __forceinline__ void emit_step(const uint32_t (&lo)[4], const uint32_t (&hi)[4], uint32_t mm, int rb, int ks, int lane, uint32_t units, uint2 bias2,
                                          uint8_t* scr, uint4* over, uint32_t tag) {
    scr += (rb >> 2) * BLK;
    const int wp = rb & 3;
    const int lo16 = (lane >> 3) * 128 + ((lane >> 2) & 1) * 16;
    uint8_t* const s0 = scr + BLK_S + wp * 2560 + lo16;
    uint8_t* const s1 = (uint8_t*)(over + rb * 144 * 8) + lo16;
    auto put_slot = [&](bool c, int sl, uint32_t v0, uint32_t v1, uint32_t off) {
        pub128(c, (sl < 20 ? s0 : s1) + (sl >> 2) * 512 + (sl & 3) * 32, v0, v1, off + RO_BIAS, tag);
    };
    const int r = lane >> 2, q = lane & 3, g0 = ks * 8 + q, g1 = g0 + 4;
    const uint32_t gm = __shfl_sync(~0u, mm, ks);
    const uint32_t c2 = __popc(mm & 0x55u) | (__popc(mm & 0xAAu) << 16);
    const uint32_t tot = __reduce_add_sync(~0u, c2), pre = __reduce_add_sync(~0u, lane < ks ? c2 : 0u);
    const int ne = tot & 0xFFFF, no = tot >> 16;
    const uint32_t par = (q & 1) ? 0xAAu : 0x55u;
    const int base = (q & 1) ? pre >> 16 : pre & 0xFFFF;
    const int rk0 = base + __popc(gm & par & ((1u << q) - 1)), rk1 = base + __popc(gm & par & ((16u << q) - 1));
    uint32_t a[4], rs[4], x[4], w0, w1;
    zip4(lo[0], lo[1], hi[0], hi[1], x); split_pair(x, rk0 & 1, a[0], a[1], w0, rs[0], rs[1]);
    zip4(lo[2], lo[3], hi[2], hi[3], x); split_pair(x, rk1 & 1, a[2], a[3], w1, rs[2], rs[3]);
    pub128(true, scr + ks * 2048 + wp * 512 + lane * 16, nonzero(a[0]), a[1], a[2], a[3]);
    w0 <<= 4 * q; w1 <<= 4 * q;
    w0 |= __shfl_xor_sync(~0u, w0, 1); w1 |= __shfl_xor_sync(~0u, w1, 1);
    w0 |= __shfl_xor_sync(~0u, w0, 2); w1 |= __shfl_xor_sync(~0u, w1, 2);
    if (q < 2) pub32(scr + BLK_M + (wp * KSTEPS + ks) * 64 + r * 8 + q * 4, q ? w1 : w0);
    const int em = min(ne, max(8, 16 - no)), om = min(no, 16 - em);
    const int odd = q & 1, m = odd ? om : em;
#pragma unroll
    for (int e = 0; e < 2; e++) {
        const int rk = e ? rk1 : rk0, t = 15 - rk;
        const int u = min(rk, t), in = (u >> 1) * 4 + (u & 1) + 2 * (odd ^ (rk >> 3 & 1)), out = 16 + (odd ? ne - em : 0) + rk - m;
        const int sl = rk >= m ? out : in;
        put_slot((gm >> (4 * e + q)) & 1, sl, rs[2 * e], rs[2 * e + 1], resid_off(e ? g1 : g0, rk & 1, r));
    }
    const int ntot = ne + no;
    const int ng = ntot > 16 ? (ntot + 3) >> 2 : min(4, (max(ne, no) + 1) >> 1);
    pub128(ks == 7 && q == 0, scr + BLK_I + wp * 128 + r * 16, ng | (units << 8), bias2.x, bias2.y, 0);
    const int idx = 2 * ks + (q & 1);
    const int frow = ks < 5 ? ks : ng - 1;
    const bool fill = ks < 4 ? !(idx < ((q >> 1) ? om : em) || (15 - idx) < ((q >> 1) ? em : om)) : (ks == 4 || (ks == 5 && ng > 5)) && 4 * frow + q >= ntot;
    put_slot(fill, frow * 4 + q, 0, 0, resid_off(q >> 1, q & 1, r));
}

template<int SEL> __device__ __forceinline__ void wgmma_sp(float (&d)[NACC], const uint32_t (&a)[4], uint64_t bdesc, uint32_t meta) {
    asm volatile("wgmma.mma_async.sp.sync.aligned.m64n48k32.f32.bf16.bf16 {%0, %1, %2, %3, %4, %5, %6, %7, %8, %9, %10, %11, %12, %13, %14, %15, %16, %17, %18, %19, %20, %21, %22, %23}, {%24, %25, %26, %27}, %28, %29, %30, 1, 1, 1, 0;"
        : "+f"(d[0]), "+f"(d[1]), "+f"(d[2]), "+f"(d[3]), "+f"(d[4]), "+f"(d[5]), "+f"(d[6]), "+f"(d[7]), "+f"(d[8]), "+f"(d[9]), "+f"(d[10]), "+f"(d[11]), "+f"(d[12]), "+f"(d[13]), "+f"(d[14]), "+f"(d[15]), "+f"(d[16]), "+f"(d[17]), "+f"(d[18]), "+f"(d[19]), "+f"(d[20]), "+f"(d[21]), "+f"(d[22]), "+f"(d[23])
        : "r"(a[0]), "r"(a[1]), "r"(a[2]), "r"(a[3]), "l"(bdesc), "r"(meta), "n"(SEL));
}
__device__ __forceinline__ void bar_sync(int id, int n) { asm volatile("bar.sync %0, %1;" :: "r"(id), "r"(n) : "memory"); }
__device__ __forceinline__ void bar_arrive(int id, int n) { asm volatile("bar.arrive %0, %1;" :: "r"(id), "r"(n) : "memory"); }

__device__ __forceinline__ void mbar_init(uint32_t bar, uint32_t cnt) { asm volatile("mbarrier.init.shared::cta.b64 [%0], %1;" :: "r"(bar), "r"(cnt) : "memory"); }
__device__ __forceinline__ void mbar_expect_tx(uint32_t bar, uint32_t bytes) {
    asm volatile("mbarrier.arrive.expect_tx.shared::cta.b64 _, [%0], %1;" :: "r"(bar), "r"(bytes) : "memory");
}
__device__ __forceinline__ void mbar_arrive(uint32_t bar) { asm volatile("mbarrier.arrive.shared::cta.b64 _, [%0];" :: "r"(bar) : "memory"); }
__device__ __forceinline__ void mbar_arrive_cluster(uint32_t bar) { asm volatile("mbarrier.arrive.shared::cluster.b64 _, [%0];" :: "r"(bar) : "memory"); }
__device__ __forceinline__ bool mbar_try(uint32_t bar, uint32_t parity) {
    uint32_t ok;
    asm volatile("{\n.reg .pred p;\nmbarrier.try_wait.parity.shared::cta.b64 p, [%1], %2;\nselp.u32 %0, 1, 0, p;\n}\n" : "=r"(ok) : "r"(bar), "r"(parity) : "memory");
    return ok;
}
__device__ __forceinline__ bool mbar_test(uint32_t bar, uint32_t parity) {
    uint32_t ok;
    asm volatile("{\n.reg .pred p;\nmbarrier.test_wait.parity.shared::cta.b64 p, [%1], %2;\nselp.u32 %0, 1, 0, p;\n}\n" : "=r"(ok) : "r"(bar), "r"(parity) : "memory");
    return ok;
}
__device__ __forceinline__ void fail_if(bool c) { asm volatile("{\n.reg .pred p;\nsetp.ne.u32 p, %0, 0;\n@p st.volatile.global.u32 [%1], %0;\n}\n" :: "r"((uint32_t)c), "l"(0ull) : "memory"); }
__device__ __forceinline__ void mbar_wait(uint32_t bar, uint32_t parity) {
    int n = 0;
    while (!mbar_try(bar, parity)) fail_if(++n > (1 << 20));
}
__device__ __forceinline__ void st_async(uint32_t addr, uint32_t v, uint32_t bar) {
    asm volatile("st.async.weak.shared::cluster.mbarrier::complete_tx::bytes.u32 [%0], %1, [%2];" :: "r"(addr), "r"(v), "r"(bar) : "memory");
}
__device__ __forceinline__ uint32_t mapa(uint32_t a, uint32_t cta) { uint32_t d; asm("mapa.shared::cluster.u32 %0, %1, %2;" : "=r"(d) : "r"(a), "r"(cta)); return d; }
__device__ __forceinline__ uint32_t lds32(uint32_t a) { uint32_t v; asm volatile("ld.shared.b32 %0, [%1];" : "=r"(v) : "r"(a)); return v; }
__device__ __forceinline__ uint4 lds128(uint32_t a) { uint4 v; asm volatile("ld.shared.v4.b32 {%0,%1,%2,%3}, [%4];" : "=r"(v.x), "=r"(v.y), "=r"(v.z), "=r"(v.w) : "r"(a)); return v; }
__device__ __forceinline__ uint32_t lds32v(uint32_t a) { uint32_t v; asm volatile("ld.volatile.shared.b32 %0, [%1];" : "=r"(v) : "r"(a) : "memory"); return v; }
__device__ __forceinline__ void sts32(uint32_t a, uint32_t v) { asm volatile("st.shared.b32 [%0], %1;" :: "r"(a), "r"(v) : "memory"); }
__device__ __forceinline__ uint32_t ld32(const void* a) { uint32_t v; asm volatile("ld.relaxed.gpu.global.u32 %0, [%1];" : "=r"(v) : "l"(a) : "memory"); return v; }
__device__ __forceinline__ uint4 ld128(const void* a) {
    uint4 v;
    asm volatile("{\n.reg .b64 s, t;\n.reg .b128 v;\nld.relaxed.gpu.global.L1::no_allocate.b128 v, [%4];\nmov.b128 {s, t}, v;\nmov.b64 {%0, %1}, s;\nmov.b64 {%2, %3}, t;\n}\n"
                 : "=r"(v.x), "=r"(v.y), "=r"(v.z), "=r"(v.w) : "l"(a) : "memory");
    return v;
}
__device__ __forceinline__ void ld128_if(bool c, const void* a, uint32_t& x, uint32_t& y, uint32_t& z, uint32_t& w) {
    asm volatile("{\n.reg .pred p;\n.reg .b64 s, t;\n.reg .b128 v;\nsetp.ne.u32 p, %5, 0;\nmov.b64 s, {%0, %1};\nmov.b64 t, {%2, %3};\nmov.b128 v, {s, t};\n"
                 "@p ld.relaxed.gpu.global.L1::no_allocate.b128 v, [%4];\nmov.b128 {s, t}, v;\nmov.b64 {%0, %1}, s;\nmov.b64 {%2, %3}, t;\n}\n"
                 : "+r"(x), "+r"(y), "+r"(z), "+r"(w) : "l"(a), "r"((uint32_t)c) : "memory");
}
__device__ __forceinline__ void ld32_if(bool c, const void* a, uint32_t& x) {
    asm volatile("{\n.reg .pred p;\nsetp.ne.u32 p, %2, 0;\n@p ld.relaxed.gpu.global.u32 %0, [%1];\n}\n" : "+r"(x) : "l"(a), "r"((uint32_t)c) : "memory");
}
__device__ __forceinline__ void mma_k8(float* c, uint2 a, uint32_t b) {
    asm volatile("mma.sync.aligned.m16n8k8.row.col.f32.bf16.bf16.f32 {%0,%1,%2,%3}, {%4,%5}, {%6}, {%0,%1,%2,%3};"
                 : "+f"(c[0]), "+f"(c[1]), "+f"(c[2]), "+f"(c[3]) : "r"(a.x), "r"(a.y), "r"(b));
}
__device__ __forceinline__ void mma_k16(float* d, uint2 a, uint2 a2, uint32_t b0, uint32_t b1, float c0, float c1, float c2, float c3) {
    asm volatile("mma.sync.aligned.m16n8k16.row.col.f32.bf16.bf16.f32 {%0,%1,%2,%3}, {%4,%5,%6,%7}, {%8,%9}, {%10,%11,%12,%13};"
                 : "=f"(d[0]), "=f"(d[1]), "=f"(d[2]), "=f"(d[3]) : "r"(a.x), "r"(a.y), "r"(a2.x), "r"(a2.y), "r"(b0), "r"(b1), "f"(c0), "f"(c1), "f"(c2), "f"(c3));
}
__device__ __forceinline__ uint32_t pack_bias(float lo, float hi, uint32_t bias2) {
    uint32_t p, o;
    asm("cvt.rn.bf16x2.f32 %0, %1, %2;" : "=r"(p) : "f"(hi), "f"(lo));
    asm("add.rn.bf16x2 %0, %1, %2;" : "=r"(o) : "r"(p), "r"(bias2));
    return o;
}

struct Params {
    const uint16_t* w; const uint16_t* bias; const uint8_t* x; uint4* scr; uint4* over;
    int ntok;
    int ntiles;
    int alltiles;
    int ncl;
    int nctas;
    int ne, pfd, pk;
    int ta, lead1, pw, k1, pfs, pfs2;
    int te, leade, slope1;
    uint32_t zero;
    int nh, jh, jd, rel;
    int a, amagic, nfull;
};
template <bool HELPER> __device__ __forceinline__ int place(const Params& p, int m) {
    if (HELPER) return ((m >> 1) * (p.a + 2) + ((m & 1) ? p.a + 1 : p.a >> 1));
    const int blk = (int)(((uint64_t)min(m, p.nfull) * (uint32_t)p.amagic) >> 32), r = m - blk * p.a;
    return (m + 2 * blk + (m < p.nfull && r >= (p.a >> 1)));
}

template <bool HELPER>
__global__ void __launch_bounds__(NTHREADS, 1)
spgemm_kernel(const __grid_constant__ CUtensorMap tmx, const __grid_constant__ CUtensorMap tmo, const Params p) {
    extern __shared__ unsigned char smem_raw[];
    const uint32_t sb = ((uint32_t)__cvta_generic_to_shared(smem_raw) + 1023u) & ~1023u;
    const int tid = threadIdx.x, warp = __shfl_sync(~0u, tid >> 5, 0), lane = tid & 31;
    const uint32_t tstart = now();
    const int rank = blockIdx.x % CL, cid = blockIdx.x / CL;
    const uint32_t bar_full = sb + OFF_FULL, bar_empty = sb + OFF_EMPTY, tk = sb + OFF_TK;
    uint4 wv[4];
    const int wrow = warp * 16 + (lane & 3) * 4;
    uint32_t b0, b1;
    auto prep_load = [&](int prb) {
        const uint32_t f0 = (prb >> 2) * 64;
        const uint16_t* const pa = p.w + ((uint32_t)(rank * 192 + wrow) * D + f0 + (lane >> 2) * 8);
#pragma unroll
        for (int j = 0; j < 4; j++) wv[j] = __ldg((const uint4*)(pa + j * D));
        b0 = __ldg(p.bias + (f0 + lane)); b1 = __ldg(p.bias + (f0 + 32 + lane));
    };
    if (!HELPER && warp < 12 && cid < 36) prep_load(cid);

    if (warp >= 12) {
        asm volatile("setmaxnreg.dec.sync.aligned.u32 32;");
        uint32_t epoch = 0;
        if (tid == NCONS + 32) asm volatile("ld.relaxed.gpu.global.u32 %0, [%1];" : "=r"(epoch) : "l"(&g_epoch) : "memory");
        if (tid == NCONS) {
#pragma unroll
            for (int s = 0; s < NSLOT; s++) { mbar_init(bar_full + 8 * s, 1); mbar_init(bar_empty + 8 * s, HELPER ? 3 : 3 * CL); }
            mbar_init(sb + OFF_MBAR, 1); mbar_init(sb + OFF_MBAR + 8, 1);
            mbar_init(sb + OFF_GO, HELPER ? 4 : 4 * CL); mbar_init(sb + OFF_GO + 8, HELPER ? 4 : 4 * CL); mbar_init(sb + OFF_GO + 16, HELPER ? 4 : 4 * CL); mbar_init(sb + OFF_EPOCH, 1);
            mbar_init(sb + OFF_FB, 1); mbar_init(sb + OFF_FB + 8, 1); mbar_init(sb + OFF_FB + 16, 1);
            asm volatile("fence.mbarrier_init.release.cluster;" ::: "memory");
            mbar_expect_tx(sb + OFF_MBAR, 36 * 4);
            if (!HELPER) asm volatile("griddepcontrol.launch_dependents;");
            asm volatile("prefetch.tensormap [%0];" :: "l"(&tmo) : "memory");
            asm volatile("prefetch.tensormap [%0];" :: "l"(&tmx) : "memory");
        }
        __syncwarp();
        if (HELPER) asm volatile("bar.sync 0;" ::: "memory");
        else asm volatile("barrier.cluster.arrive.relaxed.aligned;\nbarrier.cluster.wait.aligned;" ::: "memory");
        uint64_t pol;
        asm volatile("createpolicy.fractional.L2::evict_first.b64 %0, 1.0;" : "=l"(pol));
        if (warp == 12) {
            const int ntiles = HELPER ? p.alltiles - p.ntiles : p.ntiles;
            if (!HELPER && rank != 0) {
                auto phys = [&](int m) { return m < ntiles ? place<false>(p, m) : p.alltiles; };
                auto prefetch = [&](int t) {
                    const int rows = min(NT, p.ntok - t * NT), r0 = rows * (rank - 1) / 2, r1 = rows * rank / 2;
                    if (lane == 0 && r1 > r0)
                        asm volatile("cp.async.bulk.prefetch.L2.global [%0], %1;" :: "l"(p.x + (size_t)t * TILE_BYTES + r0 * (D * 2)), "r"((r1 - r0) * (D * 2)) : "memory");
                };
                const int u0 = phys(p.ncl), n0 = phys(NSLOT * p.ncl + p.ne) - u0;
                for (int k = cid; k < n0; k += p.ncl) { wait_until(tstart + p.pfd + k * p.pk / p.ncl); prefetch(u0 + k); }
                const int ua = phys(p.ta), n1 = phys(p.ta + p.lead1) - ua;
                for (int k = cid; k < n1; k += p.ncl) { wait_until(tstart + p.pw + (min(k, p.k1) * p.pfs + max(k - p.k1, 0) * p.pfs2) / p.ncl); prefetch(ua + k); }
            } else {
                const uint32_t rtk = HELPER ? tk : mapa(tk, lane < CL ? lane : 0), rfull = HELPER ? bar_full : mapa(bar_full, lane < CL ? lane : 0);
                int s = 0; uint32_t ph = 1, drawn = 0;
                for (int j = 0;; j++) {
                    if (j > 0 && j < NSLOT) {
#pragma unroll
                        for (int g = 0; g < 3; g++) if (blk_off(g) < OFF_X + (j + 1) * TILE_BYTES && blk_off(g) + BLK > OFF_X + j * TILE_BYTES) mbar_wait(sb + OFF_GO + 8 * g, 0);
                    }
                    mbar_wait(bar_empty + 8 * s, ph);
                    const int t = HELPER || j < NSLOT ? cid + j * p.ncl : (int)__shfl_sync(~0u, drawn, 0) + NSLOT * p.ncl;
                    const bool valid = t < ntiles;
                    if (valid && lane == 0) {
                        if (HELPER)
                            asm volatile("cp.async.bulk.tensor.4d.shared::cluster.global.mbarrier::complete_tx::bytes.L2::cache_hint [%0], [%1, {%3, %3, %3, %4}], [%2], %5;"
                                         :: "r"(sb + OFF_X + s * TILE_BYTES), "l"(&tmx), "r"(bar_full + 8 * s), "r"(0), "r"(place<HELPER>(p, t) * NB), "l"(pol) : "memory");
                        else
                            asm volatile("cp.async.bulk.tensor.4d.shared::cluster.global.mbarrier::complete_tx::bytes.multicast::cluster.L2::cache_hint [%0], [%1, {%3, %3, %3, %4}], [%2], %5, %6;"
                                         :: "r"(sb + OFF_X + s * TILE_BYTES), "l"(&tmx), "r"(bar_full + 8 * s), "r"(0), "r"(place<HELPER>(p, t) * NB), "h"((uint16_t)((1u << CL) - 1)), "l"(pol) : "memory");
                    }
                    if (HELPER) {
                        if (lane == 0) { sts32(tk + ((j & 7) << 2), valid ? (uint32_t)t : NO_TILE); mbar_expect_tx(bar_full + 8 * s, valid ? TILE_BYTES : 0); }
                    } else if (lane < CL) {
                        asm volatile("mbarrier.arrive.expect_tx.shared::cluster.b64 _, [%0], %1;" :: "r"(rfull + 8 * s), "r"(valid ? TILE_BYTES + 4 : 4) : "memory");
                        st_async(rtk + ((j & 7) << 2), valid ? (uint32_t)t : NO_TILE, rfull + 8 * s);
                    }
                    if (!valid) break;
                    if (!HELPER && lane == 0 && t > p.ta) {
                        auto fr = [&](int m) { const int f = m + p.leade + max(0, (p.slope1 * (p.te - m)) >> 16); return f < ntiles ? place<false>(p, f) : p.alltiles; };
                        const int u1 = fr(t);
                        for (int u = fr(t - 1); u < u1; u++)
                            asm volatile("cp.async.bulk.prefetch.L2.global [%0], %1;" :: "l"(p.x + (size_t)u * TILE_BYTES), "r"(min(NT, p.ntok - u * NT) * (D * 2)) : "memory");
                    }
                    if (!HELPER && lane == 0 && j >= NSLOT - 1) drawn = atomicInc(&g_ticket, ntiles - p.ncl * (NSLOT - 1) - 1);
                    if (++s == NSLOT) { s = 0; ph ^= 1; }
                }
            }
        } else {
            const int g = warp - 13;
            const uint32_t rempty = HELPER ? bar_empty : mapa(bar_empty, 0);
            if (g == 0 && lane == 0) { sts32(sb + OFF_EPOCH + 8, epoch); mbar_arrive(sb + OFF_EPOCH); }
            mbar_wait(bar_full, 0);
            uint32_t t = lds32v(tk), ph = 0;
            int s = 0, nheld = 0, nout = 0, hnext = HELPER || p.nh == 0 ? -1 : p.jh;
            uint32_t held[NH > 0 ? NH : 1];
            auto store = [&](int buf, uint32_t tile) {
                asm volatile("cp.async.bulk.tensor.2d.global.shared::cta.bulk_group.L2::cache_hint [%0, {%2, %3}], [%1], %4;"
                             :: "l"(&tmo), "r"(sb + OFF_STG + (buf * 3 + g) * STG_BYTES), "r"((g * 3 + rank) * 64), "r"((place<HELPER>(p, tile)) * NT), "l"(pol) : "memory");
            };
            auto release = [&]() {
#pragma unroll
                for (int k = 0; k < NH; k++) if (k >= nout && k < nheld && lane == 0) store(1 + k, held[k]);
                nout = nheld;
            };
            for (int i = 0;; i++) {
                bar_sync(BAR_SFULL + g, 160);
                const int s1 = s + 1 == NSLOT ? 0 : s + 1;
                if (s1 == 0) ph ^= 1;
                if (lane == 0) { if (HELPER) mbar_arrive(bar_empty + 8 * s); else mbar_arrive_cluster(rempty + 8 * s); }
                const bool ready = __all_sync(~0u, mbar_test(bar_full + 8 * s1, ph));
                if (ready) bar_arrive(BAR_G + g, 288);
                if (lane == 0) {
                    asm volatile("fence.proxy.async.shared::cta;" ::: "memory");
                    if (i != hnext) store(0, t);
                    asm volatile("cp.async.bulk.commit_group;" ::: "memory");
                    if (g == 2 && i == 0 && atomicInc(&g_passed, p.nctas - 1) == (uint32_t)p.nctas - 1) atomicAdd(&g_epoch, 1);
                }
                __syncwarp();
                if (i == hnext) {
#pragma unroll
                    for (int k = 0; k < NH; k++) if (k == nheld) held[k] = t;
                    hnext = ++nheld < p.nh ? hnext + p.jd : -1;
                }
                s = s1;
                if (!ready) { mbar_wait(bar_full + 8 * s, ph); bar_arrive(BAR_G + g, 288); }
                t = lds32v(tk + (((i + 1) & 7) << 2));
                if (t >= (uint32_t)p.rel && nout < nheld) { release(); if (lane == 0) asm volatile("cp.async.bulk.commit_group;" ::: "memory"); }
                if (lane == 0) asm volatile("cp.async.bulk.wait_group.read 0;" ::: "memory");
                __syncwarp();
                if (t == NO_TILE) break;
                bar_arrive(BAR_SEMPTY + g, 160);
            }
        }
        __syncwarp();
        if (!HELPER) asm volatile("barrier.cluster.arrive.relaxed.aligned;\nbarrier.cluster.wait.aligned;" ::: "memory");
    } else {
        asm volatile("setmaxnreg.inc.sync.aligned.u32 160;");
        const int wg = warp >> 2, r = lane >> 2, q = lane & 3;
        uint32_t epoch;
        if (HELPER) asm volatile("bar.sync 0;" ::: "memory");
        else {
            int prb = cid;
            asm volatile("barrier.cluster.arrive.relaxed.aligned;" ::: "memory");
            if (prb >= 36) asm volatile("barrier.cluster.wait.aligned;" ::: "memory");
#pragma unroll 1
            for (int round = 0; prb < 36; prb += p.ncl, round++) {
                const uint32_t wsm = sb + OFF_WST, msk = sb + OFF_MSK + (round & 1) * 144, mbar = sb + OFF_MBAR + (round & 1) * 8;
                if (round) {
                    bar_sync(3, 384);
                    if (tid == 0) mbar_expect_tx(mbar, 36 * 4);
                    prep_load(prb);
                }
                const uint32_t tk2 = min2(min2(tie_key(wv[0].x, wv[1].x, wv[2].x, wv[3].x), tie_key(wv[0].y, wv[1].y, wv[2].y, wv[3].y)),
                                          min2(tie_key(wv[0].z, wv[1].z, wv[2].z, wv[3].z), tie_key(wv[0].w, wv[1].w, wv[2].w, wv[3].w)));
                const uint32_t mk = __ballot_sync(~0u, (tk2 & 0xFFFFu) == 0 || tk2 < 0x10000u);
                if (round == 0) asm volatile("barrier.cluster.wait.aligned;" ::: "memory");
                if (lane < CL) st_async(mapa(msk + (rank * 12 + warp) * 4, lane), mk, mapa(mbar, lane));
#pragma unroll
                for (int j = 0; j < 4; j++) {
                    const int row = wrow + j;
                    const uint32_t ad = wsm + row * 128 + (((lane >> 2) ^ ((row & 1) | ((row >> 1) & 6))) << 4);
                    asm volatile("st.shared.v4.b32 [%0], {%1,%2,%3,%4};" :: "r"(ad), "r"(wv[j].x), "r"(wv[j].y), "r"(wv[j].z), "r"(wv[j].w) : "memory");
                }
                if (warp >= 6) bar_arrive(1, 384);
                else {
                    bar_sync(1, 384);
                    mbar_wait(sb + OFF_EPOCH, 0);
                    epoch = lds32v(sb + OFF_EPOCH + 8);
                    uint8_t* const scr = (uint8_t*)p.scr + (epoch & 1) * SCR_END;
                    mbar_wait(mbar, (round >> 1) & 1);
                    uint32_t m0 = 0, m1 = 0;
                    if (lane < KSTEPS) asm volatile("ld.volatile.shared.v2.b32 {%0,%1}, [%2];" : "=r"(m0), "=r"(m1) : "r"(msk + 8 * lane) : "memory");
                    uint32_t c0 = m0 - ((m0 >> 1) & 0x55555555u), c1 = m1 - ((m1 >> 1) & 0x55555555u);
                    c0 = (c0 & 0x33333333u) + ((c0 >> 2) & 0x33333333u) + (c1 & 0x33333333u) + ((c1 >> 2) & 0x33333333u);
                    c1 = __reduce_add_sync(~0u, (c0 >> 4) & 0x0F0F0F0Fu); c0 = __reduce_add_sync(~0u, c0 & 0x0F0F0F0Fu);
                    auto key = [&](int v) { return ((((v & 1) ? c1 : c0) >> (4 * (v & 6))) & 0xFFu) * 8 + v; };
                    const uint32_t ku = key(lane & 7);
                    const uint32_t l0 = __ballot_sync(~0u, key(lane >> 3) < ku), l1 = __ballot_sync(~0u, key(4 + (lane >> 3)) < ku);
                    const int rk = __popc((l0 >> (lane & 7)) & 0x01010101u) + __popc((l1 >> (lane & 7)) & 0x01010101u);
                    const int pp = prb & 3;
                    const int ulo = __ffs(__ballot_sync(~0u, rk == pp)) - 1, uhi = __ffs(__ballot_sync(~0u, rk == 7 - pp)) - 1;
                    uint32_t lo[4], hi[4];
                    load_unit(wsm, warp, ulo, lane, lo); load_unit(wsm, warp, uhi, lane, hi);
                    const uint32_t mm = (((m0 >> (4 * ulo)) | (m0 >> (4 * uhi))) & 15u) | ((((m1 >> (4 * ulo)) | (m1 >> (4 * uhi))) & 15u) << 4);
                    const uint2 bias2 = make_uint2(__shfl_sync(~0u, ulo < 4 ? b0 : b1, (ulo * 8 + r) & 31) * 0x10001u, __shfl_sync(~0u, uhi < 4 ? b0 : b1, (uhi * 8 + r) & 31) * 0x10001u);
                    emit_step(lo, hi, mm, prb, rank * 6 + warp, lane, ulo | (uhi << 4), bias2, scr, p.over, epoch + 1);
                }
            }
            if (cid >= 36 || warp >= 6) { mbar_wait(sb + OFF_EPOCH, 0); epoch = lds32v(sb + OFF_EPOCH + 8); }
            if (warp >= 6) for (int i = blockIdx.x * 192 + tid - 192; i < SCR_END / 16; i += gridDim.x * 192) p.scr[(~epoch & 1) * (SCR_END / 16) + i] = make_uint4(0, 0, 0, 0);
        }
        if (HELPER) { mbar_wait(sb + OFF_EPOCH, 0); epoch = lds32v(sb + OFF_EPOCH + 8); }
        if (wg == 2) bar_arrive(BAR_T, 256);
        const int mt = wg * 3 + rank, rb = mt * 4 + (warp & 3);
        const uint8_t* const scr = (const uint8_t*)p.scr + (epoch & 1) * SCR_END + mt * BLK;
        const int fo = (warp & 3) * 512 + lane * 16, io = BLK_I + (warp & 3) * 128 + r * 16, sl = (r >> 1) * 8 + q * 2 + (r & 1), so = BLK_S + (warp & 3) * 2560 + sl * 16;
        const int mo = BLK_M + ((warp & 3) * KSTEPS + (q >> 1)) * 64 + r * 8 + (q & 1) * 4;
        if (!HELPER && cid < 36) bar_sync(2, 384);
        const uint32_t blk = sb + blk_off(wg);
        if (warp == 0) {
            if (HELPER || cid >= 36 || p.ncl < 36) for (int n = 0; __any_sync(~0u, ld32(scr + 17 * 2048 + fo) == 0); n++) fail_if(n > (1 << 22));
            if (lane < 3) {
                mbar_expect_tx(sb + OFF_FB + 8 * lane, BLK);
                asm volatile("cp.async.bulk.shared::cluster.global.mbarrier::complete_tx::bytes [%0], [%1], %2, [%3];"
                             :: "r"(sb + blk_off(lane)), "l"(scr + lane * 3 * BLK), "r"(BLK), "r"(sb + OFF_FB + 8 * lane) : "memory");
            }
        }
        uint32_t a[KSTEPS][4], meta[9];
        uint2 rv[5]; uint32_t ro[5];
        uint32_t info, bias_lo, bias_hi;
        {
            const uint8_t* const fp = scr + fo; const uint8_t* const ip = scr + io; const uint8_t* const sp = scr + so; const uint8_t* const mp = scr + mo;
            mbar_wait(sb + OFF_FB + 8 * wg, 0);
            uint4 i0 = lds128(blk + io), sv[5];
#pragma unroll
            for (int j = 0; j < 5; j++) sv[j] = lds128(blk + so + j * 512);
#pragma unroll
            for (int j = 0; j < 9; j++) meta[j] = lds32(blk + mo + j * 128);
#pragma unroll
            for (int k = 0; k < KSTEPS; k++) { const uint4 v = lds128(blk + fo + k * 2048); a[k][0] = v.x; a[k][1] = v.y; a[k][2] = v.z; a[k][3] = v.w; }
            for (int n = 0;; n++) {
                uint32_t lo = __vimin3_u32(__vimin3_u32(i0.x, meta[8], sv[0].z), sv[1].z, __vimin3_u32(sv[2].z, sv[3].z, sv[4].z));
#pragma unroll
                for (int j = 0; j < 8; j += 2) lo = __vimin3_u32(lo, meta[j], meta[j + 1]);
#pragma unroll
                for (int k = 0; k < KSTEPS; k += 2) lo = __vimin3_u32(lo, a[k][0], a[k + 1][0]);
                if (__all_sync(~0u, lo != 0)) break;
                fail_if(n > (1 << 20));
                ld128_if(i0.x == 0, ip, i0.x, i0.y, i0.z, i0.w);
#pragma unroll
                for (int j = 0; j < 5; j++) ld128_if(sv[j].z == 0, sp + j * 512, sv[j].x, sv[j].y, sv[j].z, sv[j].w);
#pragma unroll
                for (int j = 0; j < 9; j++) ld32_if(meta[j] == 0, mp + j * 128, meta[j]);
#pragma unroll
                for (int k = 0; k < KSTEPS; k++) ld128_if(a[k][0] == 0, fp + k * 2048, a[k][0], a[k][1], a[k][2], a[k][3]);
            }
            info = i0.x; bias_lo = i0.y; bias_hi = i0.z;
#pragma unroll
            for (int j = 0; j < 5; j++) { rv[j] = make_uint2(sv[j].x, sv[j].y); ro[j] = sv[j].z; }
        }
#pragma unroll
        for (int j = 0; j < 4; j++) { rv[j].x ^= p.zero; rv[j].y ^= p.zero; }
        if ((wg || !BLK_FITS) && lane == 0) { if (HELPER) mbar_arrive(sb + OFF_GO + 8 * wg); else mbar_arrive_cluster(mapa(sb + OFF_GO + 8 * wg, 0)); }
        info = __shfl_sync(~0u, info, 0);
        const int ngrp = info & 0xFF, ulo = (info >> 8) & 7, uhi = (info >> 12) & 7;
#pragma unroll 1
        for (int j = 5; j < ngrp; j++)
            for (int n = 0; __any_sync(~0u, ld128(p.over + (rb * 36 + j) * 32 + sl).w != epoch + 1); n++) fail_if(n > (1 << 20));
        mbar_wait(bar_full, 0);
        const uint32_t stg = sb + OFF_STG + wg * STG_BYTES + ((lane >> 4) * 8 + (lane & 7)) * 128 + (((((lane >> 3) & 1) ? uhi : ulo) ^ (lane & 7)) << 4);
        float acc[NACC];
        uint32_t bq[NB][2], b4[NB];
        auto gather = [&](uint32_t xb) {
#pragma unroll
            for (int j = 0; j < 3; j++)
#pragma unroll
                for (int n = 0; n < NB; n++) { const uint32_t v = lds32(xb + ro[j] + (n * 9216 - RO_BIAS)); if (j < 2) acc[4 * n + j] = __uint_as_float(v); else bq[n][0] = v; }
            if (ngrp > 3) {
#pragma unroll
                for (int n = 0; n < NB; n++) bq[n][1] = lds32(xb + ro[3] + (n * 9216 - RO_BIAS));
                if (ngrp > 4) {
#pragma unroll
                    for (int n = 0; n < NB; n++) b4[n] = lds32(xb + ro[4] + (n * 9216 - RO_BIAS));
                }
            }
        };
        const int me = tid >> 7, nxt = __shfl_sync(~0u, BAR_T + (me == 2 ? 0 : me + 1), 0), prv = __shfl_sync(~0u, BAR_G + (me == 0 ? 2 : me - 1), 0);
#pragma unroll
        for (int n = 0; n < NB; n++) b4[n] = bq[n][1] = 0;
        gather(sb + OFF_X);
        bar_sync(BAR_T + wg, 256);
        auto bdesc = [](uint32_t x) { return ((uint64_t)1 << 62) | ((uint64_t)(9216 >> 4) << 32) | ((uint64_t)1 << 16) | (uint64_t)(x >> 4); };
        uint32_t xb = sb + OFF_X;
        uint64_t desc = bdesc(xb);
        int hnext = HELPER || p.nh == 0 ? -1 : p.jh, hbuf = 3 * STG_BYTES;
        bool more = true;
        for (int i = 0; more; i++) {
            auto rows03 = [&]() {
#pragma unroll
                for (int n = 0; n < NB; n++) mma_k16(acc + 4 * n, rv[0], rv[1], __float_as_uint(acc[4 * n]), __float_as_uint(acc[4 * n + 1]), 0.f, 0.f, 0.f, 0.f);
#pragma unroll
                for (int n = 0; n < NB; n++) mma_k16(acc + 4 * n, rv[2], rv[3], bq[n][0], bq[n][1], acc[4 * n], acc[4 * n + 1], acc[4 * n + 2], acc[4 * n + 3]);
            };
            if (ngrp <= 4) rows03();
            else {
                rows03();
#pragma unroll
                for (int n = 0; n < NB; n++) mma_k8(acc + 4 * n, rv[4], b4[n]);
#pragma unroll 1
                for (int j = 5; j < ngrp; j++) {
                    const uint4 o = __ldca(p.over + (rb * 36 + j) * 32 + sl);
#pragma unroll
                    for (int n = 0; n < NB; n++) b4[n] = lds32(xb + o.z + (n * 9216 - RO_BIAS));
#pragma unroll
                    for (int n = 0; n < NB; n++) mma_k8(acc + 4 * n, make_uint2(o.x, o.y), b4[n]);
                }
            }
            asm volatile("wgmma.fence.sync.aligned;" ::: "memory");
#pragma unroll
            for (int k = 0; k < KSTEPS; k++) {
                const uint64_t d = desc + (uint64_t)(((k >> 1) * 1024 + (k & 1) * 64) >> 4);
                if (k & 1) wgmma_sp<1>(acc, a[k], d, meta[k >> 1]);
                else       wgmma_sp<0>(acc, a[k], d, meta[k >> 1]);
                if (k == SPLIT - 1) asm volatile("wgmma.commit_group.sync.aligned;" ::: "memory");
            }
            asm volatile("wgmma.commit_group.sync.aligned;" ::: "memory");
            bar_arrive(nxt, 256);
            xb = xb == sb + OFF_X + (NSLOT - 1) * TILE_BYTES ? sb + OFF_X : xb + TILE_BYTES;
            desc = bdesc(xb);
            uint32_t sq = stg;
            if (i == hnext) { sq += hbuf; hbuf += 3 * STG_BYTES; hnext = hbuf <= p.nh * 3 * STG_BYTES ? hnext + p.jd : -1; }
            asm volatile("wgmma.wait_group.sync.aligned 1;" ::: "memory");
            if (wg != 0 || i != 0) bar_arrive(prv, 288);
            if (i != 0) bar_sync(BAR_SEMPTY + me, 160);
            asm volatile("wgmma.wait_group.sync.aligned 0;" ::: "memory");
#pragma unroll
            for (int n = 0; n + 1 < NB; n += 2) {
                const uint32_t p0 = pack_bias(acc[4 * n], acc[4 * n + 1], bias_lo), p1 = pack_bias(acc[4 * n + 2], acc[4 * n + 3], bias_hi);
                const uint32_t p2 = pack_bias(acc[4 * n + 4], acc[4 * n + 5], bias_lo), p3 = pack_bias(acc[4 * n + 6], acc[4 * n + 7], bias_hi);
                asm volatile("stmatrix.sync.aligned.m8n8.x4.trans.shared.b16 [%0], {%1,%2,%3,%4};" :: "r"(sq + n * 1024), "r"(p0), "r"(p1), "r"(p2), "r"(p3) : "memory");
            }
            if (NB & 1) {
                const uint32_t p0 = pack_bias(acc[NACC - 4], acc[NACC - 3], bias_lo), p1 = pack_bias(acc[NACC - 2], acc[NACC - 1], bias_hi);
                asm volatile("stmatrix.sync.aligned.m8n8.x2.trans.shared.b16 [%0], {%1,%2};" :: "r"(sq + (NB - 1) * 1024), "r"(p0), "r"(p1) : "memory");
            }
            bar_arrive(BAR_SFULL + me, 160);
            bar_sync(BAR_G + me, 288);
            const uint32_t tn = lds32v(tk + (((i + 1) & 7) << 2));
            gather(xb);
            more = __any_sync(~0u, tn != NO_TILE);
            if (more || wg == 0) bar_sync(BAR_T + me, 256);
        }
        if (wg == 0) bar_arrive(BAR_G + 2, 288);
        __syncwarp();
        if (!HELPER) asm volatile("barrier.cluster.arrive.relaxed.aligned;\nbarrier.cluster.wait.aligned;" ::: "memory");
    }
}

typedef CUresult (*EncodeFn)(CUtensorMap*, CUtensorMapDataType, cuuint32_t, void*, const cuuint64_t*, const cuuint64_t*, const cuuint32_t*, const cuuint32_t*,
                             CUtensorMapInterleave, CUtensorMapSwizzle, CUtensorMapL2promotion, CUtensorMapFloatOOBfill);

extern "C" void kernel_launch(void* const* d_in, const int* in_sizes, int n_in, void* d_out, int out_size) {
    static EncodeFn enc = nullptr;
    static int ncl = 0, nhelp = 0;
    const int ntok = in_sizes[0] / D;
    cudaLaunchConfig_t cfg = {};
    cudaLaunchAttribute at[1];
    at[0].id = cudaLaunchAttributeClusterDimension; at[0].val.clusterDim.x = CL; at[0].val.clusterDim.y = 1; at[0].val.clusterDim.z = 1;
    cfg.blockDim = dim3(NTHREADS); cfg.dynamicSmemBytes = SMEM_BYTES; cfg.attrs = at; cfg.numAttrs = 1; cfg.stream = cudaStreamPerThread;
    if (!enc) {
        cudaDriverEntryPointQueryResult qr; void* fn = nullptr;
        cudaGetDriverEntryPoint("cuTensorMapEncodeTiled", &fn, cudaEnableDefault, &qr);
        enc = (EncodeFn)fn;
        cudaFuncSetAttribute(spgemm_kernel<false>, cudaFuncAttributeMaxDynamicSharedMemorySize, SMEM_BYTES);
        cudaFuncSetAttribute(spgemm_kernel<true>, cudaFuncAttributeMaxDynamicSharedMemorySize, SMEM_BYTES);
        int dev = 0, nsm = 0;
        cudaGetDevice(&dev);
        cudaDeviceGetAttribute(&nsm, cudaDevAttrMultiProcessorCount, dev);
        cfg.gridDim = dim3(CL * (nsm / CL));
        cudaOccupancyMaxActiveClusters(&ncl, spgemm_kernel<false>, &cfg);
        if (ncl < 1) ncl = 1;
        nhelp = nsm > CL * ncl ? (nsm - CL * ncl) / CL : 0;
    }
    CUtensorMap tmx, tmo;
    {
        cuuint64_t dims[4] = {64, 8, 9, (cuuint64_t)(ntok / 8)};
        cuuint64_t strides[3] = {D * 2, 128, 8 * D * 2};
        cuuint32_t box[4] = {64, 8, 9, NB}, es[4] = {1, 1, 1, 1};
        enc(&tmx, CU_TENSOR_MAP_DATA_TYPE_BFLOAT16, 4, d_in[0], dims, strides, box, es, CU_TENSOR_MAP_INTERLEAVE_NONE,
            CU_TENSOR_MAP_SWIZZLE_128B, CU_TENSOR_MAP_L2_PROMOTION_L2_128B, CU_TENSOR_MAP_FLOAT_OOB_FILL_NONE);
    }
    {
        cuuint64_t dims[2] = {D, (cuuint64_t)ntok};
        cuuint64_t strides[1] = {D * 2};
        cuuint32_t box[2] = {64, NT}, es[2] = {1, 1};
        enc(&tmo, CU_TENSOR_MAP_DATA_TYPE_BFLOAT16, 2, d_out, dims, strides, box, es, CU_TENSOR_MAP_INTERLEAVE_NONE,
            CU_TENSOR_MAP_SWIZZLE_128B, CU_TENSOR_MAP_L2_PROMOTION_NONE, CU_TENSOR_MAP_FLOAT_OOB_FILL_NONE);
    }
    Params p;
    p.w = (const uint16_t*)d_in[1]; p.bias = (const uint16_t*)d_in[2]; p.x = (const uint8_t*)d_in[0];
    p.ntok = ntok;
    cudaGetSymbolAddress((void**)&p.scr, g_scr); cudaGetSymbolAddress((void**)&p.over, g_over);
    p.zero = 0;
    p.alltiles = (ntok + NT - 1) / NT;
    const int nc = ncl < p.alltiles ? ncl : p.alltiles;
    p.a = nhelp ? (int)(2 * nc / (nhelp * 1.07) + 0.5) : 2;
    if (p.a < 2) p.a = 2;
    const int nblk = (int)(p.alltiles / (p.a + 2) * 0.6);
    const int nh = nhelp && 2 * nblk >= nhelp && p.alltiles - 2 * nblk >= nc ? nhelp : 0;
    p.ntiles = p.alltiles - (nh ? 2 * nblk : 0);
    p.nfull = nh ? nblk * p.a : 0; p.amagic = (int)(0xFFFFFFFFu / (uint32_t)p.a + 1);
    p.ncl = nc; p.nctas = CL * (nc + nh);
    p.nh = (int)NH; p.jh = 4; p.jd = 4; p.rel = p.ntiles - 50;
    auto tiles = [](double v) { return (int)(v * 56 / NT); };
    auto ns = [](double v) { return (int)(v * NT / 56); };
    p.ne = tiles(0); p.pfd = 1500; p.pk = ns(900);
    p.ta = (int)(p.ntiles * 0.4) + 1; p.lead1 = tiles(250); p.pw = 3000;
    p.k1 = tiles(39); p.pfs = ns(1000); p.pfs2 = ns(2300);
    p.te = (int)(p.ntiles * 1.0) + 2; p.leade = tiles(50); p.slope1 = ((p.lead1 - p.leade) << 16) / (p.te - p.ta);
    cfg.gridDim = dim3(CL * nc);
    cudaLaunchKernelEx(&cfg, spgemm_kernel<false>, tmx, tmo, p);
    if (nh) {
        at[0].id = cudaLaunchAttributeProgrammaticStreamSerialization; at[0].val.programmaticStreamSerializationAllowed = 1;
        cfg.gridDim = dim3(CL * nh);
        p.ncl = nh;
        cudaLaunchKernelEx(&cfg, spgemm_kernel<true>, tmx, tmo, p);
    }
}
```

```cpp
#include <cuda_runtime.h>
#include <cuda_bf16.h>
#include <cuda.h>
#include <stdint.h>

constexpr int D = 576;
constexpr int NH = 2;
constexpr int NT = 48;
constexpr int NSLOT = 3;
constexpr int SPLIT = 13;
constexpr int KSTEPS = 18;
constexpr int CL = 3;
constexpr int TILE_BYTES = NT * D * 2;
constexpr int STG_BYTES = NT * 128;
constexpr int NACC = NT / 2;
constexpr int NB = NT / 8;
constexpr int NCONS = 384;
constexpr int NTHREADS = 512;
constexpr uint32_t NO_TILE = 0xFFFFFFFFu;

constexpr int OFF_X = 0;
constexpr int OFF_STG = OFF_X + NSLOT * TILE_BYTES;
constexpr int OFF_WST = OFF_STG;
constexpr int OFF_FULL = OFF_STG + (1 + NH) * 3 * STG_BYTES;
constexpr int OFF_EMPTY = OFF_FULL + 8 * NSLOT;
constexpr int OFF_MBAR = OFF_EMPTY + 8 * NSLOT;
constexpr int OFF_GO = OFF_MBAR + 16;
constexpr int OFF_FB = OFF_GO + 24;
constexpr int OFF_EPOCH = OFF_FB + 24;
constexpr int OFF_TK = OFF_EPOCH + 16;
constexpr int OFF_MSK = OFF_TK + 32;
constexpr int SMEM_BYTES = OFF_MSK + 2 * 36 * 4 + 1024;
static_assert(SMEM_BYTES <= 232448 && NSLOT < 8 && NSLOT >= 3, "layout");
constexpr int BAR_T = 4, BAR_SFULL = 7, BAR_SEMPTY = 10, BAR_G = 13;

constexpr int BLK_M = KSTEPS * 2048, BLK_S = BLK_M + 4 * KSTEPS * 64, BLK_I = BLK_S + 4 * 2560, BLK = BLK_I + 4 * 128, SCR_END = 9 * BLK;
constexpr bool BLK_FITS = BLK <= TILE_BYTES && BLK <= OFF_FULL - OFF_STG;
__host__ __device__ constexpr int blk_off(int g) { return BLK_FITS ? (g == 0 ? OFF_STG : OFF_X + g * TILE_BYTES) : OFF_X + TILE_BYTES + (g + 2) % 3 * BLK; }
static_assert(blk_off(0) + BLK <= OFF_FULL && blk_off(2) + BLK <= OFF_STG && OFF_WST + 192 * 128 <= OFF_FULL, "fragment blocks");
__device__ __align__(128) uint4    g_scr[2][SCR_END / 16];
__device__ __align__(128) uint4    g_over[36 * 144 * 8];
__device__ __align__(128) uint32_t g_epoch;
__device__ __align__(128) uint32_t g_passed;
__device__ __align__(128) uint32_t g_ticket;

__device__ __forceinline__ uint32_t now() { uint32_t c; asm volatile("mov.u32 %0, %%globaltimer_lo;" : "=r"(c)); return c; }
__device__ __forceinline__ void wait_until(uint32_t due) { while ((int)(now() - due) < 0) __nanosleep(20); }

__device__ __forceinline__ uint32_t max2(uint32_t a, uint32_t b) { uint32_t d; asm("max.u16x2 %0, %1, %2;" : "=r"(d) : "r"(a), "r"(b)); return d; }
__device__ __forceinline__ uint32_t min2(uint32_t a, uint32_t b) { uint32_t d; asm("min.u16x2 %0, %1, %2;" : "=r"(d) : "r"(a), "r"(b)); return d; }
__device__ __forceinline__ uint32_t sign2(uint32_t a) { uint32_t d; asm("prmt.b32 %0, %1, %1, 0xBB99;" : "=r"(d) : "r"(a)); return d; }
__device__ __forceinline__ void zip4(uint32_t a01, uint32_t a23, uint32_t b01, uint32_t b23, uint32_t (&x)[4]) {
    x[0] = __byte_perm(a01, b01, 0x5410); x[1] = __byte_perm(a01, b01, 0x7632); x[2] = __byte_perm(a23, b23, 0x5410); x[3] = __byte_perm(a23, b23, 0x7632);
}
__device__ __forceinline__ void middle2(const uint32_t (&x)[4], uint32_t (&m)[4], uint32_t& u, uint32_t& v) {
#pragma unroll
    for (int i = 0; i < 4; i++) m[i] = x[i] & 0x7FFF7FFFu;
    u = min2(max2(m[0], m[1]), max2(m[2], m[3])); v = max2(min2(m[0], m[1]), min2(m[2], m[3]));
}
__device__ __forceinline__ uint32_t tie_key(uint32_t x0, uint32_t x1, uint32_t x2, uint32_t x3) {
    const uint32_t x[4] = {x0, x1, x2, x3};
    uint32_t m[4], u, v;
    middle2(x, m, u, v);
    return max2(u, 0x00010001u) ^ v;
}
__device__ __forceinline__ void load_unit(uint32_t wsm, int ls, int unit, int lane, uint32_t (&m)[4]) {
    const int row = ls * 32 + (lane >> 4) * 16 + ((lane & 7) >> 1) * 4 + ((lane >> 3) & 1) * 2 + (lane & 1);
    const uint32_t ad = wsm + row * 128 + ((unit ^ ((row & 1) | ((row >> 1) & 6))) << 4);
    asm volatile("ldmatrix.sync.aligned.m8n8.x4.trans.shared.b16 {%0,%1,%2,%3}, [%4];" : "=r"(m[0]), "=r"(m[1]), "=r"(m[2]), "=r"(m[3]) : "r"(ad) : "memory");
}
__device__ __forceinline__ void split_pair(const uint32_t (&x)[4], bool P, uint32_t& alo, uint32_t& ahi, uint32_t& nib, uint32_t& rlo, uint32_t& rhi) {
    uint32_t m[4], u, v;
    middle2(x, m, u, v);
    const uint32_t c = 0x80008000u - max2(max2(u, v), 0x00010001u);
    uint32_t k0 = sign2(m[0] + c), k1 = sign2(m[1] + c), k2 = sign2(m[2] + c), k3 = sign2(m[3] + c);
    const uint32_t three = (k0 & k1 & (k2 | k3)) | (k2 & k3 & (k0 | k1)), four = k0 & k1 & k2 & k3;
    const uint32_t pa = P ? k2 : k0, pb = P ? k3 : k1;
    const uint32_t ra = three & pa, rb = three & pb & (four | ~pa);
    const uint32_t va = (P ? x[2] : x[0]) & ra, vb = (P ? x[3] : x[1]) & rb;
    if (P) { k2 &= ~ra; k3 &= ~rb; } else { k0 &= ~ra; k1 &= ~rb; }
    const uint32_t s1 = k1 & k0, s2 = k2 & (k0 | k1);
    const uint32_t t = (k1 & x[1]) | (~k1 & k2 & x[2]);
    const uint32_t x0 = (k0 & x[0]) | (~k0 & t), x1 = (s1 & x[1]) | (s2 & x[2]) | (k3 & x[3]);
    nib = (~k0 & k1 & 0x00010001u) | (~k0 & ~k1 & 0x00020002u) | (~s2 & 0x00040004u) | (~s1 & 0x00080008u);
    alo = __byte_perm(x0, x1, 0x5410); ahi = __byte_perm(x0, x1, 0x7632);
    rlo = __byte_perm(va, vb, 0x5410); rhi = __byte_perm(va, vb, 0x7632);
}
__device__ __forceinline__ uint32_t nonzero(uint32_t v) { return v ? v : 0x8000u; }
__device__ __forceinline__ void pub32(void* a, uint32_t v) { asm volatile("st.relaxed.gpu.global.u32 [%0], %1;" :: "l"(a), "r"(v) : "memory"); }
__device__ __forceinline__ void pub128(bool c, void* a, uint32_t x, uint32_t y, uint32_t z, uint32_t w) {
    asm volatile("{\n.reg .pred p;\n.reg .b64 s, t;\n.reg .b128 v;\nsetp.ne.u32 p, %5, 0;\nmov.b64 s, {%1, %2};\nmov.b64 t, {%3, %4};\nmov.b128 v, {s, t};\n@p st.relaxed.gpu.global.b128 [%0], v;\n}\n"
                 :: "l"(a), "r"(x), "r"(y), "r"(z), "r"(w), "r"((uint32_t)c) : "memory");
}
constexpr int RO_BIAS = 16;
__device__ __forceinline__ uint32_t resid_off(int g, int P, int r) {
    int k0 = 4 * g + 2 * P;
    int chunk = k0 >> 6, byte = (k0 & 63) * 2;
    return chunk * 1024 + r * 128 + (((byte >> 4) ^ r) << 4) + (byte & 15);
}
__device__ __forceinline__ void emit_step(const uint32_t (&lo)[4], const uint32_t (&hi)[4], uint32_t mm, int rb, int ks, int lane, uint32_t units, uint2 bias2,
                                          uint8_t* scr, uint4* over, uint32_t tag) {
    scr += (rb >> 2) * BLK;
    const int wp = rb & 3;
    const int lo16 = (lane >> 3) * 128 + ((lane >> 2) & 1) * 16;
    uint8_t* const s0 = scr + BLK_S + wp * 2560 + lo16;
    uint8_t* const s1 = (uint8_t*)(over + rb * 144 * 8) + lo16;
    auto put_slot = [&](bool c, int sl, uint32_t v0, uint32_t v1, uint32_t off) {
        pub128(c, (sl < 20 ? s0 : s1) + (sl >> 2) * 512 + (sl & 3) * 32, v0, v1, off + RO_BIAS, tag);
    };
    const int r = lane >> 2, q = lane & 3, g0 = ks * 8 + q, g1 = g0 + 4;
    const uint32_t gm = __shfl_sync(~0u, mm, ks);
    const uint32_t c2 = __popc(mm & 0x55u) | (__popc(mm & 0xAAu) << 16);
    const uint32_t tot = __reduce_add_sync(~0u, c2), pre = __reduce_add_sync(~0u, lane < ks ? c2 : 0u);
    const int ne = tot & 0xFFFF, no = tot >> 16;
    const uint32_t par = (q & 1) ? 0xAAu : 0x55u;
    const int base = (q & 1) ? pre >> 16 : pre & 0xFFFF;
    const int rk0 = base + __popc(gm & par & ((1u << q) - 1)), rk1 = base + __popc(gm & par & ((16u << q) - 1));
    uint32_t a[4], rs[4], x[4], w0, w1;
    zip4(lo[0], lo[1], hi[0], hi[1], x); split_pair(x, rk0 & 1, a[0], a[1], w0, rs[0], rs[1]);
    zip4(lo[2], lo[3], hi[2], hi[3], x); split_pair(x, rk1 & 1, a[2], a[3], w1, rs[2], rs[3]);
    pub128(true, scr + ks * 2048 + wp * 512 + lane * 16, nonzero(a[0]), a[1], a[2], a[3]);
    w0 <<= 4 * q; w1 <<= 4 * q;
    w0 |= __shfl_xor_sync(~0u, w0, 1); w1 |= __shfl_xor_sync(~0u, w1, 1);
    w0 |= __shfl_xor_sync(~0u, w0, 2); w1 |= __shfl_xor_sync(~0u, w1, 2);
    if (q < 2) pub32(scr + BLK_M + (wp * KSTEPS + ks) * 64 + r * 8 + q * 4, q ? w1 : w0);
    const int em = min(ne, max(8, 16 - no)), om = min(no, 16 - em);
    const int odd = q & 1, m = odd ? om : em;
#pragma unroll
    for (int e = 0; e < 2; e++) {
        const int rk = e ? rk1 : rk0, t = 15 - rk;
        const int u = min(rk, t), in = (u >> 1) * 4 + (u & 1) + 2 * (odd ^ (rk >> 3 & 1)), out = 16 + (odd ? ne - em : 0) + rk - m;
        const int sl = rk >= m ? out : in;
        put_slot((gm >> (4 * e + q)) & 1, sl, rs[2 * e], rs[2 * e + 1], resid_off(e ? g1 : g0, rk & 1, r));
    }
    const int ntot = ne + no;
    const int ng = ntot > 16 ? (ntot + 3) >> 2 : min(4, (max(ne, no) + 1) >> 1);
    pub128(ks == 7 && q == 0, scr + BLK_I + wp * 128 + r * 16, ng | (units << 8), bias2.x, bias2.y, 0);
    const int idx = 2 * ks + (q & 1);
    const int frow = ks < 5 ? ks : ng - 1;
    const bool fill = ks < 4 ? !(idx < ((q >> 1) ? om : em) || (15 - idx) < ((q >> 1) ? em : om)) : (ks == 4 || (ks == 5 && ng > 5)) && 4 * frow + q >= ntot;
    put_slot(fill, frow * 4 + q, 0, 0, resid_off(q >> 1, q & 1, r));
}

template<int SEL> __device__ __forceinline__ void wgmma_sp(float (&d)[NACC], const uint32_t (&a)[4], uint64_t bdesc, uint32_t meta) {
    asm volatile("wgmma.mma_async.sp.sync.aligned.m64n48k32.f32.bf16.bf16 {%0, %1, %2, %3, %4, %5, %6, %7, %8, %9, %10, %11, %12, %13, %14, %15, %16, %17, %18, %19, %20, %21, %22, %23}, {%24, %25, %26, %27}, %28, %29, %30, 1, 1, 1, 0;"
        : "+f"(d[0]), "+f"(d[1]), "+f"(d[2]), "+f"(d[3]), "+f"(d[4]), "+f"(d[5]), "+f"(d[6]), "+f"(d[7]), "+f"(d[8]), "+f"(d[9]), "+f"(d[10]), "+f"(d[11]), "+f"(d[12]), "+f"(d[13]), "+f"(d[14]), "+f"(d[15]), "+f"(d[16]), "+f"(d[17]), "+f"(d[18]), "+f"(d[19]), "+f"(d[20]), "+f"(d[21]), "+f"(d[22]), "+f"(d[23])
        : "r"(a[0]), "r"(a[1]), "r"(a[2]), "r"(a[3]), "l"(bdesc), "r"(meta), "n"(SEL));
}
__device__ __forceinline__ void bar_sync(int id, int n) { asm volatile("bar.sync %0, %1;" :: "r"(id), "r"(n) : "memory"); }
__device__ __forceinline__ void bar_arrive(int id, int n) { asm volatile("bar.arrive %0, %1;" :: "r"(id), "r"(n) : "memory"); }

__device__ __forceinline__ void mbar_init(uint32_t bar, uint32_t cnt) { asm volatile("mbarrier.init.shared::cta.b64 [%0], %1;" :: "r"(bar), "r"(cnt) : "memory"); }
__device__ __forceinline__ void mbar_expect_tx(uint32_t bar, uint32_t bytes) {
    asm volatile("mbarrier.arrive.expect_tx.shared::cta.b64 _, [%0], %1;" :: "r"(bar), "r"(bytes) : "memory");
}
__device__ __forceinline__ void mbar_arrive(uint32_t bar) { asm volatile("mbarrier.arrive.shared::cta.b64 _, [%0];" :: "r"(bar) : "memory"); }
__device__ __forceinline__ void mbar_arrive_cluster(uint32_t bar) { asm volatile("mbarrier.arrive.shared::cluster.b64 _, [%0];" :: "r"(bar) : "memory"); }
__device__ __forceinline__ bool mbar_try(uint32_t bar, uint32_t parity) {
    uint32_t ok;
    asm volatile("{\n.reg .pred p;\nmbarrier.try_wait.parity.shared::cta.b64 p, [%1], %2;\nselp.u32 %0, 1, 0, p;\n}\n" : "=r"(ok) : "r"(bar), "r"(parity) : "memory");
    return ok;
}
__device__ __forceinline__ bool mbar_test(uint32_t bar, uint32_t parity) {
    uint32_t ok;
    asm volatile("{\n.reg .pred p;\nmbarrier.test_wait.parity.shared::cta.b64 p, [%1], %2;\nselp.u32 %0, 1, 0, p;\n}\n" : "=r"(ok) : "r"(bar), "r"(parity) : "memory");
    return ok;
}
__device__ __forceinline__ void fail_if(bool c) { asm volatile("{\n.reg .pred p;\nsetp.ne.u32 p, %0, 0;\n@p st.volatile.global.u32 [%1], %0;\n}\n" :: "r"((uint32_t)c), "l"(0ull) : "memory"); }
__device__ __forceinline__ void mbar_wait(uint32_t bar, uint32_t parity) {
    int n = 0;
    while (!mbar_try(bar, parity)) fail_if(++n > (1 << 20));
}
__device__ __forceinline__ void st_async(uint32_t addr, uint32_t v, uint32_t bar) {
    asm volatile("st.async.weak.shared::cluster.mbarrier::complete_tx::bytes.u32 [%0], %1, [%2];" :: "r"(addr), "r"(v), "r"(bar) : "memory");
}
__device__ __forceinline__ uint32_t mapa(uint32_t a, uint32_t cta) { uint32_t d; asm("mapa.shared::cluster.u32 %0, %1, %2;" : "=r"(d) : "r"(a), "r"(cta)); return d; }
__device__ __forceinline__ uint32_t lds32(uint32_t a) { uint32_t v; asm volatile("ld.shared.b32 %0, [%1];" : "=r"(v) : "r"(a)); return v; }
__device__ __forceinline__ uint4 lds128(uint32_t a) { uint4 v; asm volatile("ld.shared.v4.b32 {%0,%1,%2,%3}, [%4];" : "=r"(v.x), "=r"(v.y), "=r"(v.z), "=r"(v.w) : "r"(a)); return v; }
__device__ __forceinline__ uint32_t lds32v(uint32_t a) { uint32_t v; asm volatile("ld.volatile.shared.b32 %0, [%1];" : "=r"(v) : "r"(a) : "memory"); return v; }
__device__ __forceinline__ void sts32(uint32_t a, uint32_t v) { asm volatile("st.shared.b32 [%0], %1;" :: "r"(a), "r"(v) : "memory"); }
__device__ __forceinline__ uint32_t ld32(const void* a) { uint32_t v; asm volatile("ld.relaxed.gpu.global.u32 %0, [%1];" : "=r"(v) : "l"(a) : "memory"); return v; }
__device__ __forceinline__ uint4 ld128(const void* a) {
    uint4 v;
    asm volatile("{\n.reg .b64 s, t;\n.reg .b128 v;\nld.relaxed.gpu.global.L1::no_allocate.b128 v, [%4];\nmov.b128 {s, t}, v;\nmov.b64 {%0, %1}, s;\nmov.b64 {%2, %3}, t;\n}\n"
                 : "=r"(v.x), "=r"(v.y), "=r"(v.z), "=r"(v.w) : "l"(a) : "memory");
    return v;
}
__device__ __forceinline__ void ld128_if(bool c, const void* a, uint32_t& x, uint32_t& y, uint32_t& z, uint32_t& w) {
    asm volatile("{\n.reg .pred p;\n.reg .b64 s, t;\n.reg .b128 v;\nsetp.ne.u32 p, %5, 0;\nmov.b64 s, {%0, %1};\nmov.b64 t, {%2, %3};\nmov.b128 v, {s, t};\n"
                 "@p ld.relaxed.gpu.global.L1::no_allocate.b128 v, [%4];\nmov.b128 {s, t}, v;\nmov.b64 {%0, %1}, s;\nmov.b64 {%2, %3}, t;\n}\n"
                 : "+r"(x), "+r"(y), "+r"(z), "+r"(w) : "l"(a), "r"((uint32_t)c) : "memory");
}
__device__ __forceinline__ void ld32_if(bool c, const void* a, uint32_t& x) {
    asm volatile("{\n.reg .pred p;\nsetp.ne.u32 p, %2, 0;\n@p ld.relaxed.gpu.global.u32 %0, [%1];\n}\n" : "+r"(x) : "l"(a), "r"((uint32_t)c) : "memory");
}
__device__ __forceinline__ void mma_k8(float* c, uint2 a, uint32_t b) {
    asm volatile("mma.sync.aligned.m16n8k8.row.col.f32.bf16.bf16.f32 {%0,%1,%2,%3}, {%4,%5}, {%6}, {%0,%1,%2,%3};"
                 : "+f"(c[0]), "+f"(c[1]), "+f"(c[2]), "+f"(c[3]) : "r"(a.x), "r"(a.y), "r"(b));
}
__device__ __forceinline__ void mma_k16(float* d, uint2 a, uint2 a2, uint32_t b0, uint32_t b1, float c0, float c1, float c2, float c3) {
    asm volatile("mma.sync.aligned.m16n8k16.row.col.f32.bf16.bf16.f32 {%0,%1,%2,%3}, {%4,%5,%6,%7}, {%8,%9}, {%10,%11,%12,%13};"
                 : "=f"(d[0]), "=f"(d[1]), "=f"(d[2]), "=f"(d[3]) : "r"(a.x), "r"(a.y), "r"(a2.x), "r"(a2.y), "r"(b0), "r"(b1), "f"(c0), "f"(c1), "f"(c2), "f"(c3));
}
__device__ __forceinline__ uint32_t pack_bias(float lo, float hi, uint32_t bias2) {
    uint32_t p, o;
    asm("cvt.rn.bf16x2.f32 %0, %1, %2;" : "=r"(p) : "f"(hi), "f"(lo));
    asm("add.rn.bf16x2 %0, %1, %2;" : "=r"(o) : "r"(p), "r"(bias2));
    return o;
}

struct Params {
    const uint16_t* w; const uint16_t* bias; const uint8_t* x; uint4* scr; uint4* over;
    int ntok;
    int ntiles;
    int alltiles;
    int ncl;
    int nctas;
    int pfd, pk;
    int ta, lead1, pw, k1, pfs, pfs2;
    int te, leade, slope1;
    uint32_t zero;
    int nh, jh, jd, rel;
    int a, amagic, nfull;
};
template <bool HELPER> __device__ __forceinline__ int place(const Params& p, int m) {
    if (HELPER) return ((m >> 1) * (p.a + 2) + ((m & 1) ? p.a + 1 : p.a >> 1));
    const int blk = (int)(((uint64_t)min(m, p.nfull) * (uint32_t)p.amagic) >> 32), r = m - blk * p.a;
    return (m + 2 * blk + (m < p.nfull && r >= (p.a >> 1)));
}

template <bool HELPER>
__global__ void __launch_bounds__(NTHREADS, 1)
spgemm_kernel(const __grid_constant__ CUtensorMap tmx, const __grid_constant__ CUtensorMap tmo, const Params p) {
    extern __shared__ unsigned char smem_raw[];
    const uint32_t sb = ((uint32_t)__cvta_generic_to_shared(smem_raw) + 1023u) & ~1023u;
    const int tid = threadIdx.x, warp = __shfl_sync(~0u, tid >> 5, 0), lane = tid & 31;
    const uint32_t tstart = now();
    const int rank = blockIdx.x % CL, cid = blockIdx.x / CL;
    const uint32_t bar_full = sb + OFF_FULL, bar_empty = sb + OFF_EMPTY, tk = sb + OFF_TK;
    uint4 wv[4];
    const int wrow = warp * 16 + (lane & 3) * 4;
    uint32_t b0, b1;
    auto prep_load = [&](int prb) {
        const uint32_t f0 = (prb >> 2) * 64;
        const uint16_t* const pa = p.w + ((uint32_t)(rank * 192 + wrow) * D + f0 + (lane >> 2) * 8);
#pragma unroll
        for (int j = 0; j < 4; j++) wv[j] = __ldg((const uint4*)(pa + j * D));
        b0 = __ldg(p.bias + (f0 + lane)); b1 = __ldg(p.bias + (f0 + 32 + lane));
    };
    if (!HELPER && warp < 12 && cid < 36) prep_load(cid);

    if (warp >= 12) {
        asm volatile("setmaxnreg.dec.sync.aligned.u32 32;");
        uint32_t epoch = 0;
        if (tid == NCONS + 32) asm volatile("ld.relaxed.gpu.global.u32 %0, [%1];" : "=r"(epoch) : "l"(&g_epoch) : "memory");
        if (tid == NCONS) {
#pragma unroll
            for (int s = 0; s < NSLOT; s++) { mbar_init(bar_full + 8 * s, 1); mbar_init(bar_empty + 8 * s, HELPER ? 3 : 3 * CL); }
            mbar_init(sb + OFF_MBAR, 1); mbar_init(sb + OFF_MBAR + 8, 1);
            mbar_init(sb + OFF_GO, HELPER ? 4 : 4 * CL); mbar_init(sb + OFF_GO + 8, HELPER ? 4 : 4 * CL); mbar_init(sb + OFF_GO + 16, HELPER ? 4 : 4 * CL); mbar_init(sb + OFF_EPOCH, 1);
            mbar_init(sb + OFF_FB, 1); mbar_init(sb + OFF_FB + 8, 1); mbar_init(sb + OFF_FB + 16, 1);
            asm volatile("fence.mbarrier_init.release.cluster;" ::: "memory");
            mbar_expect_tx(sb + OFF_MBAR, 36 * 4);
            if (!HELPER) asm volatile("griddepcontrol.launch_dependents;");
            asm volatile("prefetch.tensormap [%0];" :: "l"(&tmo) : "memory");
            asm volatile("prefetch.tensormap [%0];" :: "l"(&tmx) : "memory");
        }
        __syncwarp();
        if (HELPER) asm volatile("bar.sync 0;" ::: "memory");
        else asm volatile("barrier.cluster.arrive.relaxed.aligned;\nbarrier.cluster.wait.aligned;" ::: "memory");
        uint64_t pol;
        asm volatile("createpolicy.fractional.L2::evict_first.b64 %0, 1.0;" : "=l"(pol));
        if (warp == 12) {
            const int ntiles = HELPER ? p.alltiles - p.ntiles : p.ntiles;
            if (!HELPER && rank != 0) {
                auto phys = [&](int m) { return m < ntiles ? place<false>(p, m) : p.alltiles; };
                auto prefetch = [&](int t) {
                    const int rows = min(NT, p.ntok - t * NT), r0 = rows * (rank - 1) / 2, r1 = rows * rank / 2;
                    if (lane == 0 && r1 > r0)
                        asm volatile("cp.async.bulk.prefetch.L2.global [%0], %1;" :: "l"(p.x + (size_t)t * TILE_BYTES + r0 * (D * 2)), "r"((r1 - r0) * (D * 2)) : "memory");
                };
                const int u0 = phys(p.ncl), n0 = phys(NSLOT * p.ncl) - u0;
                for (int k = cid; k < n0; k += p.ncl) { wait_until(tstart + p.pfd + k * p.pk / p.ncl); prefetch(u0 + k); }
                const int ua = phys(p.ta), n1 = phys(p.ta + p.lead1) - ua;
                for (int k = cid; k < n1; k += p.ncl) { wait_until(tstart + p.pw + (min(k, p.k1) * p.pfs + max(k - p.k1, 0) * p.pfs2) / p.ncl); prefetch(ua + k); }
            } else {
                const uint32_t rtk = HELPER ? tk : mapa(tk, lane < CL ? lane : 0), rfull = HELPER ? bar_full : mapa(bar_full, lane < CL ? lane : 0);
                int s = 0; uint32_t ph = 1, drawn = 0;
                for (int j = 0;; j++) {
                    if (j > 0 && j < NSLOT) {
#pragma unroll
                        for (int g = 0; g < 3; g++) if (blk_off(g) < OFF_X + (j + 1) * TILE_BYTES && blk_off(g) + BLK > OFF_X + j * TILE_BYTES) mbar_wait(sb + OFF_GO + 8 * g, 0);
                    }
                    mbar_wait(bar_empty + 8 * s, ph);
                    const int t = HELPER || j < NSLOT ? cid + j * p.ncl : (int)__shfl_sync(~0u, drawn, 0) + NSLOT * p.ncl;
                    const bool valid = t < ntiles;
                    if (valid && lane == 0) {
                        if (HELPER)
                            asm volatile("cp.async.bulk.tensor.4d.shared::cluster.global.mbarrier::complete_tx::bytes.L2::cache_hint [%0], [%1, {%3, %3, %3, %4}], [%2], %5;"
                                         :: "r"(sb + OFF_X + s * TILE_BYTES), "l"(&tmx), "r"(bar_full + 8 * s), "r"(0), "r"(place<HELPER>(p, t) * NB), "l"(pol) : "memory");
                        else
                            asm volatile("cp.async.bulk.tensor.4d.shared::cluster.global.mbarrier::complete_tx::bytes.multicast::cluster.L2::cache_hint [%0], [%1, {%3, %3, %3, %4}], [%2], %5, %6;"
                                         :: "r"(sb + OFF_X + s * TILE_BYTES), "l"(&tmx), "r"(bar_full + 8 * s), "r"(0), "r"(place<HELPER>(p, t) * NB), "h"((uint16_t)((1u << CL) - 1)), "l"(pol) : "memory");
                    }
                    if (HELPER) {
                        if (lane == 0) { sts32(tk + ((j & 7) << 2), valid ? (uint32_t)t : NO_TILE); mbar_expect_tx(bar_full + 8 * s, valid ? TILE_BYTES : 0); }
                    } else if (lane < CL) {
                        asm volatile("mbarrier.arrive.expect_tx.shared::cluster.b64 _, [%0], %1;" :: "r"(rfull + 8 * s), "r"(valid ? TILE_BYTES + 4 : 4) : "memory");
                        st_async(rtk + ((j & 7) << 2), valid ? (uint32_t)t : NO_TILE, rfull + 8 * s);
                    }
                    if (!valid) break;
                    if (!HELPER && lane == 0 && t > p.ta) {
                        auto fr = [&](int m) { const int f = m + p.leade + max(0, (p.slope1 * (p.te - m)) >> 16); return f < ntiles ? place<false>(p, f) : p.alltiles; };
                        const int u1 = fr(t);
                        for (int u = fr(t - 1); u < u1; u++)
                            asm volatile("cp.async.bulk.prefetch.L2.global [%0], %1;" :: "l"(p.x + (size_t)u * TILE_BYTES), "r"(min(NT, p.ntok - u * NT) * (D * 2)) : "memory");
                    }
                    if (!HELPER && lane == 0 && j >= NSLOT - 1) drawn = atomicInc(&g_ticket, ntiles - p.ncl * (NSLOT - 1) - 1);
                    if (++s == NSLOT) { s = 0; ph ^= 1; }
                }
            }
        } else {
            const int g = warp - 13;
            const uint32_t rempty = HELPER ? bar_empty : mapa(bar_empty, 0);
            if (g == 0 && lane == 0) { sts32(sb + OFF_EPOCH + 8, epoch); mbar_arrive(sb + OFF_EPOCH); }
            mbar_wait(bar_full, 0);
            uint32_t t = lds32v(tk), ph = 0;
            int s = 0, nheld = 0, nout = 0, hnext = HELPER || p.nh == 0 ? -1 : p.jh;
            uint32_t held[NH > 0 ? NH : 1];
            auto store = [&](int buf, uint32_t tile) {
                asm volatile("cp.async.bulk.tensor.2d.global.shared::cta.bulk_group.L2::cache_hint [%0, {%2, %3}], [%1], %4;"
                             :: "l"(&tmo), "r"(sb + OFF_STG + (buf * 3 + g) * STG_BYTES), "r"((g * 3 + rank) * 64), "r"((place<HELPER>(p, tile)) * NT), "l"(pol) : "memory");
            };
            auto release = [&]() {
#pragma unroll
                for (int k = 0; k < NH; k++) if (k >= nout && k < nheld && lane == 0) store(1 + k, held[k]);
                nout = nheld;
            };
            for (int i = 0;; i++) {
                bar_sync(BAR_SFULL + g, 160);
                const int s1 = s + 1 == NSLOT ? 0 : s + 1;
                if (s1 == 0) ph ^= 1;
                if (lane == 0) { if (HELPER) mbar_arrive(bar_empty + 8 * s); else mbar_arrive_cluster(rempty + 8 * s); }
                const bool ready = __all_sync(~0u, mbar_test(bar_full + 8 * s1, ph));
                if (ready) bar_arrive(BAR_G + g, 288);
                if (lane == 0) {
                    asm volatile("fence.proxy.async.shared::cta;" ::: "memory");
                    if (i != hnext) store(0, t);
                    asm volatile("cp.async.bulk.commit_group;" ::: "memory");
                    if (g == 2 && i == 0 && atomicInc(&g_passed, p.nctas - 1) == (uint32_t)p.nctas - 1) atomicAdd(&g_epoch, 1);
                }
                __syncwarp();
                if (i == hnext) {
#pragma unroll
                    for (int k = 0; k < NH; k++) if (k == nheld) held[k] = t;
                    hnext = ++nheld < p.nh ? hnext + p.jd : -1;
                }
                s = s1;
                if (!ready) { mbar_wait(bar_full + 8 * s, ph); bar_arrive(BAR_G + g, 288); }
                t = lds32v(tk + (((i + 1) & 7) << 2));
                if (t >= (uint32_t)p.rel && nout < nheld) { release(); if (lane == 0) asm volatile("cp.async.bulk.commit_group;" ::: "memory"); }
                if (lane == 0) asm volatile("cp.async.bulk.wait_group.read 0;" ::: "memory");
                __syncwarp();
                if (t == NO_TILE) break;
                bar_arrive(BAR_SEMPTY + g, 160);
            }
        }
        __syncwarp();
        if (!HELPER) asm volatile("barrier.cluster.arrive.relaxed.aligned;\nbarrier.cluster.wait.aligned;" ::: "memory");
    } else {
        asm volatile("setmaxnreg.inc.sync.aligned.u32 160;");
        const int wg = warp >> 2, r = lane >> 2, q = lane & 3;
        uint32_t epoch;
        if (HELPER) asm volatile("bar.sync 0;" ::: "memory");
        else {
            int prb = cid;
            asm volatile("barrier.cluster.arrive.relaxed.aligned;" ::: "memory");
            if (prb >= 36) asm volatile("barrier.cluster.wait.aligned;" ::: "memory");
#pragma unroll 1
            for (int round = 0; prb < 36; prb += p.ncl, round++) {
                const uint32_t wsm = sb + OFF_WST, msk = sb + OFF_MSK + (round & 1) * 144, mbar = sb + OFF_MBAR + (round & 1) * 8;
                if (round) {
                    bar_sync(3, 384);
                    if (tid == 0) mbar_expect_tx(mbar, 36 * 4);
                    prep_load(prb);
                }
                const uint32_t tk2 = min2(min2(tie_key(wv[0].x, wv[1].x, wv[2].x, wv[3].x), tie_key(wv[0].y, wv[1].y, wv[2].y, wv[3].y)),
                                          min2(tie_key(wv[0].z, wv[1].z, wv[2].z, wv[3].z), tie_key(wv[0].w, wv[1].w, wv[2].w, wv[3].w)));
                const uint32_t mk = __ballot_sync(~0u, (tk2 & 0xFFFFu) == 0 || tk2 < 0x10000u);
                if (round == 0) asm volatile("barrier.cluster.wait.aligned;" ::: "memory");
                if (lane < CL) st_async(mapa(msk + (rank * 12 + warp) * 4, lane), mk, mapa(mbar, lane));
#pragma unroll
                for (int j = 0; j < 4; j++) {
                    const int row = wrow + j;
                    const uint32_t ad = wsm + row * 128 + (((lane >> 2) ^ ((row & 1) | ((row >> 1) & 6))) << 4);
                    asm volatile("st.shared.v4.b32 [%0], {%1,%2,%3,%4};" :: "r"(ad), "r"(wv[j].x), "r"(wv[j].y), "r"(wv[j].z), "r"(wv[j].w) : "memory");
                }
                if (warp >= 6) bar_arrive(1, 384);
                else {
                    bar_sync(1, 384);
                    mbar_wait(sb + OFF_EPOCH, 0);
                    epoch = lds32v(sb + OFF_EPOCH + 8);
                    uint8_t* const scr = (uint8_t*)p.scr + (epoch & 1) * SCR_END;
                    mbar_wait(mbar, (round >> 1) & 1);
                    uint32_t m0 = 0, m1 = 0;
                    if (lane < KSTEPS) asm volatile("ld.volatile.shared.v2.b32 {%0,%1}, [%2];" : "=r"(m0), "=r"(m1) : "r"(msk + 8 * lane) : "memory");
                    uint32_t c0 = m0 - ((m0 >> 1) & 0x55555555u), c1 = m1 - ((m1 >> 1) & 0x55555555u);
                    c0 = (c0 & 0x33333333u) + ((c0 >> 2) & 0x33333333u) + (c1 & 0x33333333u) + ((c1 >> 2) & 0x33333333u);
                    c1 = __reduce_add_sync(~0u, (c0 >> 4) & 0x0F0F0F0Fu); c0 = __reduce_add_sync(~0u, c0 & 0x0F0F0F0Fu);
                    auto key = [&](int v) { return ((((v & 1) ? c1 : c0) >> (4 * (v & 6))) & 0xFFu) * 8 + v; };
                    const uint32_t ku = key(lane & 7);
                    const uint32_t l0 = __ballot_sync(~0u, key(lane >> 3) < ku), l1 = __ballot_sync(~0u, key(4 + (lane >> 3)) < ku);
                    const int rk = __popc((l0 >> (lane & 7)) & 0x01010101u) + __popc((l1 >> (lane & 7)) & 0x01010101u);
                    const int pp = prb & 3;
                    const int ulo = __ffs(__ballot_sync(~0u, rk == pp)) - 1, uhi = __ffs(__ballot_sync(~0u, rk == 7 - pp)) - 1;
                    uint32_t lo[4], hi[4];
                    load_unit(wsm, warp, ulo, lane, lo); load_unit(wsm, warp, uhi, lane, hi);
                    const uint32_t mm = (((m0 >> (4 * ulo)) | (m0 >> (4 * uhi))) & 15u) | ((((m1 >> (4 * ulo)) | (m1 >> (4 * uhi))) & 15u) << 4);
                    const uint2 bias2 = make_uint2(__shfl_sync(~0u, ulo < 4 ? b0 : b1, (ulo * 8 + r) & 31) * 0x10001u, __shfl_sync(~0u, uhi < 4 ? b0 : b1, (uhi * 8 + r) & 31) * 0x10001u);
                    emit_step(lo, hi, mm, prb, rank * 6 + warp, lane, ulo | (uhi << 4), bias2, scr, p.over, epoch + 1);
                }
            }
            if (cid >= 36 || warp >= 6) { mbar_wait(sb + OFF_EPOCH, 0); epoch = lds32v(sb + OFF_EPOCH + 8); }
            if (warp >= 6) for (int i = blockIdx.x * 192 + tid - 192; i < SCR_END / 16; i += gridDim.x * 192) p.scr[(~epoch & 1) * (SCR_END / 16) + i] = make_uint4(0, 0, 0, 0);
        }
        if (HELPER) { mbar_wait(sb + OFF_EPOCH, 0); epoch = lds32v(sb + OFF_EPOCH + 8); }
        if (wg == 2) bar_arrive(BAR_T, 256);
        const int mt = wg * 3 + rank, rb = mt * 4 + (warp & 3);
        const uint8_t* const scr = (const uint8_t*)p.scr + (epoch & 1) * SCR_END + mt * BLK;
        const int fo = (warp & 3) * 512 + lane * 16, io = BLK_I + (warp & 3) * 128 + r * 16, sl = (r >> 1) * 8 + q * 2 + (r & 1), so = BLK_S + (warp & 3) * 2560 + sl * 16;
        const int mo = BLK_M + ((warp & 3) * KSTEPS + (q >> 1)) * 64 + r * 8 + (q & 1) * 4;
        if (!HELPER && cid < 36) bar_sync(2, 384);
        const uint32_t blk = sb + blk_off(wg);
        if (warp == 0) {
            if (HELPER || cid >= 36 || p.ncl < 36) for (int n = 0; __any_sync(~0u, ld32(scr + 17 * 2048 + fo) == 0); n++) fail_if(n > (1 << 22));
            if (lane < 3) {
                mbar_expect_tx(sb + OFF_FB + 8 * lane, BLK);
                asm volatile("cp.async.bulk.shared::cluster.global.mbarrier::complete_tx::bytes [%0], [%1], %2, [%3];"
                             :: "r"(sb + blk_off(lane)), "l"(scr + lane * 3 * BLK), "r"(BLK), "r"(sb + OFF_FB + 8 * lane) : "memory");
            }
        }
        uint32_t a[KSTEPS][4], meta[9];
        uint2 rv[5]; uint32_t ro[5];
        uint32_t info, bias_lo, bias_hi;
        {
            const uint8_t* const fp = scr + fo; const uint8_t* const ip = scr + io; const uint8_t* const sp = scr + so; const uint8_t* const mp = scr + mo;
            mbar_wait(sb + OFF_FB + 8 * wg, 0);
            uint4 i0 = lds128(blk + io), sv[5];
#pragma unroll
            for (int j = 0; j < 5; j++) sv[j] = lds128(blk + so + j * 512);
#pragma unroll
            for (int j = 0; j < 9; j++) meta[j] = lds32(blk + mo + j * 128);
#pragma unroll
            for (int k = 0; k < KSTEPS; k++) { const uint4 v = lds128(blk + fo + k * 2048); a[k][0] = v.x; a[k][1] = v.y; a[k][2] = v.z; a[k][3] = v.w; }
            for (int n = 0;; n++) {
                uint32_t lo = __vimin3_u32(__vimin3_u32(i0.x, meta[8], sv[0].z), sv[1].z, __vimin3_u32(sv[2].z, sv[3].z, sv[4].z));
#pragma unroll
                for (int j = 0; j < 8; j += 2) lo = __vimin3_u32(lo, meta[j], meta[j + 1]);
#pragma unroll
                for (int k = 0; k < KSTEPS; k += 2) lo = __vimin3_u32(lo, a[k][0], a[k + 1][0]);
                if (__all_sync(~0u, lo != 0)) break;
                fail_if(n > (1 << 20));
                ld128_if(i0.x == 0, ip, i0.x, i0.y, i0.z, i0.w);
#pragma unroll
                for (int j = 0; j < 5; j++) ld128_if(sv[j].z == 0, sp + j * 512, sv[j].x, sv[j].y, sv[j].z, sv[j].w);
#pragma unroll
                for (int j = 0; j < 9; j++) ld32_if(meta[j] == 0, mp + j * 128, meta[j]);
#pragma unroll
                for (int k = 0; k < KSTEPS; k++) ld128_if(a[k][0] == 0, fp + k * 2048, a[k][0], a[k][1], a[k][2], a[k][3]);
            }
            info = i0.x; bias_lo = i0.y; bias_hi = i0.z;
#pragma unroll
            for (int j = 0; j < 5; j++) { rv[j] = make_uint2(sv[j].x, sv[j].y); ro[j] = sv[j].z; }
        }
#pragma unroll
        for (int j = 0; j < 4; j++) { rv[j].x ^= p.zero; rv[j].y ^= p.zero; }
        if ((wg || !BLK_FITS) && lane == 0) { if (HELPER) mbar_arrive(sb + OFF_GO + 8 * wg); else mbar_arrive_cluster(mapa(sb + OFF_GO + 8 * wg, 0)); }
        info = __shfl_sync(~0u, info, 0);
        const int ngrp = info & 0xFF, ulo = (info >> 8) & 7, uhi = (info >> 12) & 7;
#pragma unroll 1
        for (int j = 5; j < ngrp; j++)
            for (int n = 0; __any_sync(~0u, ld128(p.over + (rb * 36 + j) * 32 + sl).w != epoch + 1); n++) fail_if(n > (1 << 20));
        mbar_wait(bar_full, 0);
        const uint32_t stg = sb + OFF_STG + wg * STG_BYTES + ((lane >> 4) * 8 + (lane & 7)) * 128 + (((((lane >> 3) & 1) ? uhi : ulo) ^ (lane & 7)) << 4);
        float acc[NACC];
        uint32_t bq[NB][2], b4[NB];
        auto gather = [&](uint32_t xb) {
#pragma unroll
            for (int j = 0; j < 3; j++)
#pragma unroll
                for (int n = 0; n < NB; n++) { const uint32_t v = lds32(xb + ro[j] + (n * 9216 - RO_BIAS)); if (j < 2) acc[4 * n + j] = __uint_as_float(v); else bq[n][0] = v; }
            if (ngrp > 3) {
#pragma unroll
                for (int n = 0; n < NB; n++) bq[n][1] = lds32(xb + ro[3] + (n * 9216 - RO_BIAS));
                if (ngrp > 4) {
#pragma unroll
                    for (int n = 0; n < NB; n++) b4[n] = lds32(xb + ro[4] + (n * 9216 - RO_BIAS));
                }
            }
        };
        const int me = tid >> 7, nxt = __shfl_sync(~0u, BAR_T + (me == 2 ? 0 : me + 1), 0), prv = __shfl_sync(~0u, BAR_G + (me == 0 ? 2 : me - 1), 0);
#pragma unroll
        for (int n = 0; n < NB; n++) b4[n] = bq[n][1] = 0;
        gather(sb + OFF_X);
        bar_sync(BAR_T + wg, 256);
        auto bdesc = [](uint32_t x) { return ((uint64_t)1 << 62) | ((uint64_t)(9216 >> 4) << 32) | ((uint64_t)1 << 16) | (uint64_t)(x >> 4); };
        uint32_t xb = sb + OFF_X;
        uint64_t desc = bdesc(xb);
        int hnext = HELPER || p.nh == 0 ? -1 : p.jh, hbuf = 3 * STG_BYTES;
        bool more = true;
        for (int i = 0; more; i++) {
            auto rows03 = [&]() {
#pragma unroll
                for (int n = 0; n < NB; n++) mma_k16(acc + 4 * n, rv[0], rv[1], __float_as_uint(acc[4 * n]), __float_as_uint(acc[4 * n + 1]), 0.f, 0.f, 0.f, 0.f);
#pragma unroll
                for (int n = 0; n < NB; n++) mma_k16(acc + 4 * n, rv[2], rv[3], bq[n][0], bq[n][1], acc[4 * n], acc[4 * n + 1], acc[4 * n + 2], acc[4 * n + 3]);
            };
            if (ngrp <= 4) rows03();
            else {
                rows03();
#pragma unroll
                for (int n = 0; n < NB; n++) mma_k8(acc + 4 * n, rv[4], b4[n]);
#pragma unroll 1
                for (int j = 5; j < ngrp; j++) {
                    const uint4 o = __ldca(p.over + (rb * 36 + j) * 32 + sl);
#pragma unroll
                    for (int n = 0; n < NB; n++) b4[n] = lds32(xb + o.z + (n * 9216 - RO_BIAS));
#pragma unroll
                    for (int n = 0; n < NB; n++) mma_k8(acc + 4 * n, make_uint2(o.x, o.y), b4[n]);
                }
            }
            asm volatile("wgmma.fence.sync.aligned;" ::: "memory");
#pragma unroll
            for (int k = 0; k < KSTEPS; k++) {
                const uint64_t d = desc + (uint64_t)(((k >> 1) * 1024 + (k & 1) * 64) >> 4);
                if (k & 1) wgmma_sp<1>(acc, a[k], d, meta[k >> 1]);
                else       wgmma_sp<0>(acc, a[k], d, meta[k >> 1]);
                if (k == SPLIT - 1) asm volatile("wgmma.commit_group.sync.aligned;" ::: "memory");
            }
            asm volatile("wgmma.commit_group.sync.aligned;" ::: "memory");
            bar_arrive(nxt, 256);
            xb = xb == sb + OFF_X + (NSLOT - 1) * TILE_BYTES ? sb + OFF_X : xb + TILE_BYTES;
            desc = bdesc(xb);
            uint32_t sq = stg;
            if (i == hnext) { sq += hbuf; hbuf += 3 * STG_BYTES; hnext = hbuf <= p.nh * 3 * STG_BYTES ? hnext + p.jd : -1; }
            asm volatile("wgmma.wait_group.sync.aligned 1;" ::: "memory");
            if (wg != 0 || i != 0) bar_arrive(prv, 288);
            if (i != 0) bar_sync(BAR_SEMPTY + me, 160);
            asm volatile("wgmma.wait_group.sync.aligned 0;" ::: "memory");
#pragma unroll
            for (int n = 0; n + 1 < NB; n += 2) {
                const uint32_t p0 = pack_bias(acc[4 * n], acc[4 * n + 1], bias_lo), p1 = pack_bias(acc[4 * n + 2], acc[4 * n + 3], bias_hi);
                const uint32_t p2 = pack_bias(acc[4 * n + 4], acc[4 * n + 5], bias_lo), p3 = pack_bias(acc[4 * n + 6], acc[4 * n + 7], bias_hi);
                asm volatile("stmatrix.sync.aligned.m8n8.x4.trans.shared.b16 [%0], {%1,%2,%3,%4};" :: "r"(sq + n * 1024), "r"(p0), "r"(p1), "r"(p2), "r"(p3) : "memory");
            }
            if (NB & 1) {
                const uint32_t p0 = pack_bias(acc[NACC - 4], acc[NACC - 3], bias_lo), p1 = pack_bias(acc[NACC - 2], acc[NACC - 1], bias_hi);
                asm volatile("stmatrix.sync.aligned.m8n8.x2.trans.shared.b16 [%0], {%1,%2};" :: "r"(sq + (NB - 1) * 1024), "r"(p0), "r"(p1) : "memory");
            }
            bar_arrive(BAR_SFULL + me, 160);
            bar_sync(BAR_G + me, 288);
            const uint32_t tn = lds32v(tk + (((i + 1) & 7) << 2));
            gather(xb);
            more = __any_sync(~0u, tn != NO_TILE);
            if (more || wg == 0) bar_sync(BAR_T + me, 256);
        }
        if (wg == 0) bar_arrive(BAR_G + 2, 288);
        __syncwarp();
        if (!HELPER) asm volatile("barrier.cluster.arrive.relaxed.aligned;\nbarrier.cluster.wait.aligned;" ::: "memory");
    }
}

typedef CUresult (*EncodeFn)(CUtensorMap*, CUtensorMapDataType, cuuint32_t, void*, const cuuint64_t*, const cuuint64_t*, const cuuint32_t*, const cuuint32_t*,
                             CUtensorMapInterleave, CUtensorMapSwizzle, CUtensorMapL2promotion, CUtensorMapFloatOOBfill);

extern "C" void kernel_launch(void* const* d_in, const int* in_sizes, int n_in, void* d_out, int out_size) {
    static EncodeFn enc = nullptr;
    static int ncl = 0, nhelp = 0;
    const int ntok = in_sizes[0] / D;
    cudaLaunchConfig_t cfg = {};
    cudaLaunchAttribute at[1];
    at[0].id = cudaLaunchAttributeClusterDimension; at[0].val.clusterDim.x = CL; at[0].val.clusterDim.y = 1; at[0].val.clusterDim.z = 1;
    cfg.blockDim = dim3(NTHREADS); cfg.dynamicSmemBytes = SMEM_BYTES; cfg.attrs = at; cfg.numAttrs = 1; cfg.stream = cudaStreamPerThread;
    if (!enc) {
        cudaDriverEntryPointQueryResult qr; void* fn = nullptr;
        cudaGetDriverEntryPoint("cuTensorMapEncodeTiled", &fn, cudaEnableDefault, &qr);
        enc = (EncodeFn)fn;
        cudaFuncSetAttribute(spgemm_kernel<false>, cudaFuncAttributeMaxDynamicSharedMemorySize, SMEM_BYTES);
        cudaFuncSetAttribute(spgemm_kernel<true>, cudaFuncAttributeMaxDynamicSharedMemorySize, SMEM_BYTES);
        int dev = 0, nsm = 0;
        cudaGetDevice(&dev);
        cudaDeviceGetAttribute(&nsm, cudaDevAttrMultiProcessorCount, dev);
        cfg.gridDim = dim3(CL * (nsm / CL));
        cudaOccupancyMaxActiveClusters(&ncl, spgemm_kernel<false>, &cfg);
        if (ncl < 1) ncl = 1;
        nhelp = nsm > CL * ncl ? (nsm - CL * ncl) / CL : 0;
    }
    CUtensorMap tmx, tmo;
    {
        cuuint64_t dims[4] = {64, 8, 9, (cuuint64_t)(ntok / 8)};
        cuuint64_t strides[3] = {D * 2, 128, 8 * D * 2};
        cuuint32_t box[4] = {64, 8, 9, NB}, es[4] = {1, 1, 1, 1};
        enc(&tmx, CU_TENSOR_MAP_DATA_TYPE_BFLOAT16, 4, d_in[0], dims, strides, box, es, CU_TENSOR_MAP_INTERLEAVE_NONE,
            CU_TENSOR_MAP_SWIZZLE_128B, CU_TENSOR_MAP_L2_PROMOTION_L2_128B, CU_TENSOR_MAP_FLOAT_OOB_FILL_NONE);
    }
    {
        cuuint64_t dims[2] = {D, (cuuint64_t)ntok};
        cuuint64_t strides[1] = {D * 2};
        cuuint32_t box[2] = {64, NT}, es[2] = {1, 1};
        enc(&tmo, CU_TENSOR_MAP_DATA_TYPE_BFLOAT16, 2, d_out, dims, strides, box, es, CU_TENSOR_MAP_INTERLEAVE_NONE,
            CU_TENSOR_MAP_SWIZZLE_128B, CU_TENSOR_MAP_L2_PROMOTION_NONE, CU_TENSOR_MAP_FLOAT_OOB_FILL_NONE);
    }
    Params p;
    p.w = (const uint16_t*)d_in[1]; p.bias = (const uint16_t*)d_in[2]; p.x = (const uint8_t*)d_in[0];
    p.ntok = ntok;
    cudaGetSymbolAddress((void**)&p.scr, g_scr); cudaGetSymbolAddress((void**)&p.over, g_over);
    p.zero = 0;
    p.alltiles = (ntok + NT - 1) / NT;
    const int nc = ncl < p.alltiles ? ncl : p.alltiles;
    p.a = nhelp ? (int)(2 * nc / (nhelp * 1.07) + 0.5) : 2;
    if (p.a < 2) p.a = 2;
    const int nblk = (int)(p.alltiles / (p.a + 2) * 0.6);
    const int nh = nhelp && 2 * nblk >= nhelp && p.alltiles - 2 * nblk >= nc ? nhelp : 0;
    p.ntiles = p.alltiles - (nh ? 2 * nblk : 0);
    p.nfull = nh ? nblk * p.a : 0; p.amagic = (int)(0xFFFFFFFFu / (uint32_t)p.a + 1);
    p.ncl = nc; p.nctas = CL * (nc + nh);
    p.nh = (int)NH; p.jh = 4; p.jd = 4; p.rel = p.ntiles - 50;
    auto tiles = [](double v) { return (int)(v * 56 / NT); };
    auto ns = [](double v) { return (int)(v * NT / 56); };
    p.pfd = 1500; p.pk = ns(900);
    p.ta = (int)(p.ntiles * 0.4) + 1; p.lead1 = tiles(250); p.pw = 3000;
    p.k1 = tiles(68); p.pfs = ns(700); p.pfs2 = ns(2300);
    p.te = p.ntiles + 2; p.leade = tiles(50); p.slope1 = ((p.lead1 - p.leade) << 16) / (p.te - p.ta);
    cfg.gridDim = dim3(CL * nc);
    cudaLaunchKernelEx(&cfg, spgemm_kernel<false>, tmx, tmo, p);
    if (nh) {
        at[0].id = cudaLaunchAttributeProgrammaticStreamSerialization; at[0].val.programmaticStreamSerializationAllowed = 1;
        cfg.gridDim = dim3(CL * nh);
        p.ncl = nh;
        cudaLaunchKernelEx(&cfg, spgemm_kernel<true>, tmx, tmo, p);
    }
}
```

```cpp
#include <cuda_runtime.h>
#include <cuda_bf16.h>
#include <cuda.h>
#include <stdint.h>

constexpr int D = 576;
constexpr int NH = 2;
constexpr int NT = 48;
constexpr int NSLOT = 3;
constexpr int SPLIT = 13;
constexpr int KSTEPS = 18;
constexpr int CL = 3;
constexpr int TILE_BYTES = NT * D * 2;
constexpr int STG_BYTES = NT * 128;
constexpr int NACC = NT / 2;
constexpr int NB = NT / 8;
constexpr int NCONS = 384;
constexpr int NTHREADS = 512;
constexpr uint32_t NO_TILE = 0xFFFFFFFFu;

constexpr int OFF_X = 0;
constexpr int OFF_STG = OFF_X + NSLOT * TILE_BYTES;
constexpr int OFF_WST = OFF_STG;
constexpr int OFF_FULL = OFF_STG + ((1 + NH) * 3 + 1) * STG_BYTES;
constexpr int OFF_EMPTY = OFF_FULL + 8 * NSLOT;
constexpr int OFF_MBAR = OFF_EMPTY + 8 * NSLOT;
constexpr int OFF_GO = OFF_MBAR + 16;
constexpr int OFF_FB = OFF_GO + 24;
constexpr int OFF_EPOCH = OFF_FB + 24;
constexpr int OFF_TK = OFF_EPOCH + 16;
constexpr int OFF_MSK = OFF_TK + 32;
constexpr int SMEM_BYTES = OFF_MSK + 2 * 36 * 4 + 1024;
static_assert(SMEM_BYTES <= 232448 && NSLOT < 8 && NSLOT >= 3, "layout");
constexpr int BAR_T = 4, BAR_SFULL = 7, BAR_SEMPTY = 10, BAR_G = 13;

constexpr int BLK_M = KSTEPS * 2048, BLK_S = BLK_M + 4 * KSTEPS * 64, BLK_I = BLK_S + 4 * 2560, BLK = BLK_I + 4 * 128, SCR_END = 9 * BLK;
constexpr bool BLK_FITS = BLK <= TILE_BYTES && BLK <= OFF_FULL - OFF_STG;
__host__ __device__ constexpr int blk_off(int g) { return BLK_FITS ? (g == 0 ? OFF_STG : OFF_X + g * TILE_BYTES) : OFF_X + TILE_BYTES + (g + 2) % 3 * BLK; }
static_assert(blk_off(0) + BLK <= OFF_FULL && blk_off(2) + BLK <= OFF_STG && OFF_WST + 192 * 128 <= OFF_FULL, "fragment blocks");
__device__ __align__(128) uint4    g_scr[2][SCR_END / 16];
__device__ __align__(128) uint4    g_over[36 * 144 * 8];
__device__ __align__(128) uint32_t g_epoch;
__device__ __align__(128) uint32_t g_passed;
__device__ __align__(128) uint32_t g_ticket;

__device__ __forceinline__ uint32_t now() { uint32_t c; asm volatile("mov.u32 %0, %%globaltimer_lo;" : "=r"(c)); return c; }
__device__ __forceinline__ void wait_until(uint32_t due) { while ((int)(now() - due) < 0) __nanosleep(20); }

__device__ __forceinline__ uint32_t max2(uint32_t a, uint32_t b) { uint32_t d; asm("max.u16x2 %0, %1, %2;" : "=r"(d) : "r"(a), "r"(b)); return d; }
__device__ __forceinline__ uint32_t min2(uint32_t a, uint32_t b) { uint32_t d; asm("min.u16x2 %0, %1, %2;" : "=r"(d) : "r"(a), "r"(b)); return d; }
__device__ __forceinline__ uint32_t sign2(uint32_t a) { uint32_t d; asm("prmt.b32 %0, %1, %1, 0xBB99;" : "=r"(d) : "r"(a)); return d; }
__device__ __forceinline__ void zip4(uint32_t a01, uint32_t a23, uint32_t b01, uint32_t b23, uint32_t (&x)[4]) {
    x[0] = __byte_perm(a01, b01, 0x5410); x[1] = __byte_perm(a01, b01, 0x7632); x[2] = __byte_perm(a23, b23, 0x5410); x[3] = __byte_perm(a23, b23, 0x7632);
}
__device__ __forceinline__ void middle2(const uint32_t (&x)[4], uint32_t (&m)[4], uint32_t& u, uint32_t& v) {
#pragma unroll
    for (int i = 0; i < 4; i++) m[i] = x[i] & 0x7FFF7FFFu;
    u = min2(max2(m[0], m[1]), max2(m[2], m[3])); v = max2(min2(m[0], m[1]), min2(m[2], m[3]));
}
__device__ __forceinline__ uint32_t tie_key(uint32_t x0, uint32_t x1, uint32_t x2, uint32_t x3) {
    const uint32_t x[4] = {x0, x1, x2, x3};
    uint32_t m[4], u, v;
    middle2(x, m, u, v);
    return max2(u, 0x00010001u) ^ v;
}
__device__ __forceinline__ void load_unit(uint32_t wsm, int ls, int unit, int lane, uint32_t (&m)[4]) {
    const int row = ls * 32 + (lane >> 4) * 16 + ((lane & 7) >> 1) * 4 + ((lane >> 3) & 1) * 2 + (lane & 1);
    const uint32_t ad = wsm + row * 128 + ((unit ^ ((row & 1) | ((row >> 1) & 6))) << 4);
    asm volatile("ldmatrix.sync.aligned.m8n8.x4.trans.shared.b16 {%0,%1,%2,%3}, [%4];" : "=r"(m[0]), "=r"(m[1]), "=r"(m[2]), "=r"(m[3]) : "r"(ad) : "memory");
}
__device__ __forceinline__ void split_pair(const uint32_t (&x)[4], bool P, uint32_t& alo, uint32_t& ahi, uint32_t& nib, uint32_t& rlo, uint32_t& rhi) {
    uint32_t m[4], u, v;
    middle2(x, m, u, v);
    const uint32_t c = 0x80008000u - max2(max2(u, v), 0x00010001u);
    uint32_t k0 = sign2(m[0] + c), k1 = sign2(m[1] + c), k2 = sign2(m[2] + c), k3 = sign2(m[3] + c);
    const uint32_t three = (k0 & k1 & (k2 | k3)) | (k2 & k3 & (k0 | k1)), four = k0 & k1 & k2 & k3;
    const uint32_t pa = P ? k2 : k0, pb = P ? k3 : k1;
    const uint32_t ra = three & pa, rb = three & pb & (four | ~pa);
    const uint32_t va = (P ? x[2] : x[0]) & ra, vb = (P ? x[3] : x[1]) & rb;
    if (P) { k2 &= ~ra; k3 &= ~rb; } else { k0 &= ~ra; k1 &= ~rb; }
    const uint32_t s1 = k1 & k0, s2 = k2 & (k0 | k1);
    const uint32_t t = (k1 & x[1]) | (~k1 & k2 & x[2]);
    const uint32_t x0 = (k0 & x[0]) | (~k0 & t), x1 = (s1 & x[1]) | (s2 & x[2]) | (k3 & x[3]);
    nib = (~k0 & k1 & 0x00010001u) | (~k0 & ~k1 & 0x00020002u) | (~s2 & 0x00040004u) | (~s1 & 0x00080008u);
    alo = __byte_perm(x0, x1, 0x5410); ahi = __byte_perm(x0, x1, 0x7632);
    rlo = __byte_perm(va, vb, 0x5410); rhi = __byte_perm(va, vb, 0x7632);
}
__device__ __forceinline__ uint32_t nonzero(uint32_t v) { return v ? v : 0x8000u; }
__device__ __forceinline__ void pub32(void* a, uint32_t v) { asm volatile("st.relaxed.gpu.global.u32 [%0], %1;" :: "l"(a), "r"(v) : "memory"); }
__device__ __forceinline__ void pub128(bool c, void* a, uint32_t x, uint32_t y, uint32_t z, uint32_t w) {
    asm volatile("{\n.reg .pred p;\n.reg .b64 s, t;\n.reg .b128 v;\nsetp.ne.u32 p, %5, 0;\nmov.b64 s, {%1, %2};\nmov.b64 t, {%3, %4};\nmov.b128 v, {s, t};\n@p st.relaxed.gpu.global.b128 [%0], v;\n}\n"
                 :: "l"(a), "r"(x), "r"(y), "r"(z), "r"(w), "r"((uint32_t)c) : "memory");
}
constexpr int RO_BIAS = 16;
__device__ __forceinline__ uint32_t resid_off(int g, int P, int r) {
    int k0 = 4 * g + 2 * P;
    int chunk = k0 >> 6, byte = (k0 & 63) * 2;
    return chunk * 1024 + r * 128 + (((byte >> 4) ^ r) << 4) + (byte & 15);
}
__device__ __forceinline__ void emit_step(const uint32_t (&lo)[4], const uint32_t (&hi)[4], uint32_t mm, int rb, int ks, int lane, uint32_t units, uint2 bias2,
                                          uint8_t* scr, uint4* over, uint32_t tag) {
    scr += (rb >> 2) * BLK;
    const int wp = rb & 3;
    const int lo16 = (lane >> 3) * 128 + ((lane >> 2) & 1) * 16;
    uint8_t* const s0 = scr + BLK_S + wp * 2560 + lo16;
    uint8_t* const s1 = (uint8_t*)(over + rb * 144 * 8) + lo16;
    auto put_slot = [&](bool c, int sl, uint32_t v0, uint32_t v1, uint32_t off) {
        pub128(c, (sl < 20 ? s0 : s1) + (sl >> 2) * 512 + (sl & 3) * 32, v0, v1, off + RO_BIAS, tag);
    };
    const int r = lane >> 2, q = lane & 3, g0 = ks * 8 + q, g1 = g0 + 4;
    const uint32_t gm = __shfl_sync(~0u, mm, ks);
    const uint32_t c2 = __popc(mm & 0x55u) | (__popc(mm & 0xAAu) << 16);
    const uint32_t tot = __reduce_add_sync(~0u, c2), pre = __reduce_add_sync(~0u, lane < ks ? c2 : 0u);
    const int ne = tot & 0xFFFF, no = tot >> 16;
    const uint32_t par = (q & 1) ? 0xAAu : 0x55u;
    const int base = (q & 1) ? pre >> 16 : pre & 0xFFFF;
    const int rk0 = base + __popc(gm & par & ((1u << q) - 1)), rk1 = base + __popc(gm & par & ((16u << q) - 1));
    uint32_t a[4], rs[4], x[4], w0, w1;
    zip4(lo[0], lo[1], hi[0], hi[1], x); split_pair(x, rk0 & 1, a[0], a[1], w0, rs[0], rs[1]);
    zip4(lo[2], lo[3], hi[2], hi[3], x); split_pair(x, rk1 & 1, a[2], a[3], w1, rs[2], rs[3]);
    pub128(true, scr + ks * 2048 + wp * 512 + lane * 16, nonzero(a[0]), a[1], a[2], a[3]);
    w0 <<= 4 * q; w1 <<= 4 * q;
    w0 |= __shfl_xor_sync(~0u, w0, 1); w1 |= __shfl_xor_sync(~0u, w1, 1);
    w0 |= __shfl_xor_sync(~0u, w0, 2); w1 |= __shfl_xor_sync(~0u, w1, 2);
    if (q < 2) pub32(scr + BLK_M + (wp * KSTEPS + ks) * 64 + r * 8 + q * 4, q ? w1 : w0);
    const int em = min(ne, max(8, 16 - no)), om = min(no, 16 - em);
    const int odd = q & 1, m = odd ? om : em;
#pragma unroll
    for (int e = 0; e < 2; e++) {
        const int rk = e ? rk1 : rk0, t = 15 - rk;
        const int u = min(rk, t), in = (u >> 1) * 4 + (u & 1) + 2 * (odd ^ (rk >> 3 & 1)), out = 16 + (odd ? ne - em : 0) + rk - m;
        const int sl = rk >= m ? out : in;
        put_slot((gm >> (4 * e + q)) & 1, sl, rs[2 * e], rs[2 * e + 1], resid_off(e ? g1 : g0, rk & 1, r));
    }
    const int ntot = ne + no;
    const int ng = ntot > 16 ? (ntot + 3) >> 2 : min(4, (max(ne, no) + 1) >> 1);
    pub128(ks == 7 && q == 0, scr + BLK_I + wp * 128 + r * 16, ng | (units << 8), bias2.x, bias2.y, 0);
    const int idx = 2 * ks + (q & 1);
    const int frow = ks < 5 ? ks : ng - 1;
    const bool fill = ks < 4 ? !(idx < ((q >> 1) ? om : em) || (15 - idx) < ((q >> 1) ? em : om)) : (ks == 4 || (ks == 5 && ng > 5)) && 4 * frow + q >= ntot;
    put_slot(fill, frow * 4 + q, 0, 0, resid_off(q >> 1, q & 1, r));
}

template<int SEL> __device__ __forceinline__ void wgmma_sp(float (&d)[NACC], const uint32_t (&a)[4], uint64_t bdesc, uint32_t meta) {
    asm volatile("wgmma.mma_async.sp.sync.aligned.m64n48k32.f32.bf16.bf16 {%0, %1, %2, %3, %4, %5, %6, %7, %8, %9, %10, %11, %12, %13, %14, %15, %16, %17, %18, %19, %20, %21, %22, %23}, {%24, %25, %26, %27}, %28, %29, %30, 1, 1, 1, 0;"
        : "+f"(d[0]), "+f"(d[1]), "+f"(d[2]), "+f"(d[3]), "+f"(d[4]), "+f"(d[5]), "+f"(d[6]), "+f"(d[7]), "+f"(d[8]), "+f"(d[9]), "+f"(d[10]), "+f"(d[11]), "+f"(d[12]), "+f"(d[13]), "+f"(d[14]), "+f"(d[15]), "+f"(d[16]), "+f"(d[17]), "+f"(d[18]), "+f"(d[19]), "+f"(d[20]), "+f"(d[21]), "+f"(d[22]), "+f"(d[23])
        : "r"(a[0]), "r"(a[1]), "r"(a[2]), "r"(a[3]), "l"(bdesc), "r"(meta), "n"(SEL));
}
__device__ __forceinline__ void bar_sync(int id, int n) { asm volatile("bar.sync %0, %1;" :: "r"(id), "r"(n) : "memory"); }
__device__ __forceinline__ void bar_arrive(int id, int n) { asm volatile("bar.arrive %0, %1;" :: "r"(id), "r"(n) : "memory"); }

__device__ __forceinline__ void mbar_init(uint32_t bar, uint32_t cnt) { asm volatile("mbarrier.init.shared::cta.b64 [%0], %1;" :: "r"(bar), "r"(cnt) : "memory"); }
__device__ __forceinline__ void mbar_expect_tx(uint32_t bar, uint32_t bytes) {
    asm volatile("mbarrier.arrive.expect_tx.shared::cta.b64 _, [%0], %1;" :: "r"(bar), "r"(bytes) : "memory");
}
__device__ __forceinline__ void mbar_arrive(uint32_t bar) { asm volatile("mbarrier.arrive.shared::cta.b64 _, [%0];" :: "r"(bar) : "memory"); }
__device__ __forceinline__ void mbar_arrive_cluster(uint32_t bar) { asm volatile("mbarrier.arrive.shared::cluster.b64 _, [%0];" :: "r"(bar) : "memory"); }
__device__ __forceinline__ bool mbar_try(uint32_t bar, uint32_t parity) {
    uint32_t ok;
    asm volatile("{\n.reg .pred p;\nmbarrier.try_wait.parity.shared::cta.b64 p, [%1], %2;\nselp.u32 %0, 1, 0, p;\n}\n" : "=r"(ok) : "r"(bar), "r"(parity) : "memory");
    return ok;
}
__device__ __forceinline__ bool mbar_test(uint32_t bar, uint32_t parity) {
    uint32_t ok;
    asm volatile("{\n.reg .pred p;\nmbarrier.test_wait.parity.shared::cta.b64 p, [%1], %2;\nselp.u32 %0, 1, 0, p;\n}\n" : "=r"(ok) : "r"(bar), "r"(parity) : "memory");
    return ok;
}
__device__ __forceinline__ void fail_if(bool c) { asm volatile("{\n.reg .pred p;\nsetp.ne.u32 p, %0, 0;\n@p st.volatile.global.u32 [%1], %0;\n}\n" :: "r"((uint32_t)c), "l"(0ull) : "memory"); }
__device__ __forceinline__ void mbar_wait(uint32_t bar, uint32_t parity) {
    int n = 0;
    while (!mbar_try(bar, parity)) fail_if(++n > (1 << 20));
}
__device__ __forceinline__ void st_async(uint32_t addr, uint32_t v, uint32_t bar) {
    asm volatile("st.async.weak.shared::cluster.mbarrier::complete_tx::bytes.u32 [%0], %1, [%2];" :: "r"(addr), "r"(v), "r"(bar) : "memory");
}
__device__ __forceinline__ uint32_t mapa(uint32_t a, uint32_t cta) { uint32_t d; asm("mapa.shared::cluster.u32 %0, %1, %2;" : "=r"(d) : "r"(a), "r"(cta)); return d; }
__device__ __forceinline__ uint32_t lds32(uint32_t a) { uint32_t v; asm volatile("ld.shared.b32 %0, [%1];" : "=r"(v) : "r"(a)); return v; }
__device__ __forceinline__ uint4 lds128(uint32_t a) { uint4 v; asm volatile("ld.shared.v4.b32 {%0,%1,%2,%3}, [%4];" : "=r"(v.x), "=r"(v.y), "=r"(v.z), "=r"(v.w) : "r"(a)); return v; }
__device__ __forceinline__ uint32_t lds32v(uint32_t a) { uint32_t v; asm volatile("ld.volatile.shared.b32 %0, [%1];" : "=r"(v) : "r"(a) : "memory"); return v; }
__device__ __forceinline__ void sts32(uint32_t a, uint32_t v) { asm volatile("st.shared.b32 [%0], %1;" :: "r"(a), "r"(v) : "memory"); }
__device__ __forceinline__ uint32_t ld32(const void* a) { uint32_t v; asm volatile("ld.relaxed.gpu.global.u32 %0, [%1];" : "=r"(v) : "l"(a) : "memory"); return v; }
__device__ __forceinline__ uint4 ld128(const void* a) {
    uint4 v;
    asm volatile("{\n.reg .b64 s, t;\n.reg .b128 v;\nld.relaxed.gpu.global.L1::no_allocate.b128 v, [%4];\nmov.b128 {s, t}, v;\nmov.b64 {%0, %1}, s;\nmov.b64 {%2, %3}, t;\n}\n"
                 : "=r"(v.x), "=r"(v.y), "=r"(v.z), "=r"(v.w) : "l"(a) : "memory");
    return v;
}
__device__ __forceinline__ void ld128_if(bool c, const void* a, uint32_t& x, uint32_t& y, uint32_t& z, uint32_t& w) {
    asm volatile("{\n.reg .pred p;\n.reg .b64 s, t;\n.reg .b128 v;\nsetp.ne.u32 p, %5, 0;\nmov.b64 s, {%0, %1};\nmov.b64 t, {%2, %3};\nmov.b128 v, {s, t};\n"
                 "@p ld.relaxed.gpu.global.L1::no_allocate.b128 v, [%4];\nmov.b128 {s, t}, v;\nmov.b64 {%0, %1}, s;\nmov.b64 {%2, %3}, t;\n}\n"
                 : "+r"(x), "+r"(y), "+r"(z), "+r"(w) : "l"(a), "r"((uint32_t)c) : "memory");
}
__device__ __forceinline__ void ld32_if(bool c, const void* a, uint32_t& x) {
    asm volatile("{\n.reg .pred p;\nsetp.ne.u32 p, %2, 0;\n@p ld.relaxed.gpu.global.u32 %0, [%1];\n}\n" : "+r"(x) : "l"(a), "r"((uint32_t)c) : "memory");
}
__device__ __forceinline__ void mma_k8(float* c, uint2 a, uint32_t b) {
    asm volatile("mma.sync.aligned.m16n8k8.row.col.f32.bf16.bf16.f32 {%0,%1,%2,%3}, {%4,%5}, {%6}, {%0,%1,%2,%3};"
                 : "+f"(c[0]), "+f"(c[1]), "+f"(c[2]), "+f"(c[3]) : "r"(a.x), "r"(a.y), "r"(b));
}
__device__ __forceinline__ void mma_k16(float* d, uint2 a, uint2 a2, uint32_t b0, uint32_t b1, float c0, float c1, float c2, float c3) {
    asm volatile("mma.sync.aligned.m16n8k16.row.col.f32.bf16.bf16.f32 {%0,%1,%2,%3}, {%4,%5,%6,%7}, {%8,%9}, {%10,%11,%12,%13};"
                 : "=f"(d[0]), "=f"(d[1]), "=f"(d[2]), "=f"(d[3]) : "r"(a.x), "r"(a.y), "r"(a2.x), "r"(a2.y), "r"(b0), "r"(b1), "f"(c0), "f"(c1), "f"(c2), "f"(c3));
}
__device__ __forceinline__ uint32_t pack_bias(float lo, float hi, uint32_t bias2) {
    uint32_t p, o;
    asm("cvt.rn.bf16x2.f32 %0, %1, %2;" : "=r"(p) : "f"(hi), "f"(lo));
    asm("add.rn.bf16x2 %0, %1, %2;" : "=r"(o) : "r"(p), "r"(bias2));
    return o;
}

struct Params {
    const uint16_t* w; const uint16_t* bias; const uint8_t* x; uint4* scr; uint4* over;
    int ntok;
    int ntiles;
    int alltiles;
    int ncl;
    int nctas;
    int pfd, pk;
    int ta, lead1, pw, k1, pfs, pfs2;
    int te, leade, slope1;
    uint32_t zero;
    int nha, nht, trig;
    int nh, jh, jd, rel;
    int a, amagic, nfull;
};
template <bool HELPER> __device__ __forceinline__ int place(const Params& p, int m) {
    if (HELPER) return (m < p.nha ? (m >> 1) * (p.a + 2) + ((m & 1) ? p.a + 1 : p.a >> 1) : p.alltiles - p.nht - p.nha + m);
    const int blk = (int)(((uint64_t)min(m, p.nfull) * (uint32_t)p.amagic) >> 32), r = m - blk * p.a;
    return (m + 2 * blk + (m < p.nfull && r >= (p.a >> 1)));
}

template <bool HELPER>
__global__ void __launch_bounds__(NTHREADS, 1)
spgemm_kernel(const __grid_constant__ CUtensorMap tmx, const __grid_constant__ CUtensorMap tmo, const Params p) {
    extern __shared__ unsigned char smem_raw[];
    const uint32_t sb = ((uint32_t)__cvta_generic_to_shared(smem_raw) + 1023u) & ~1023u;
    const int tid = threadIdx.x, warp = __shfl_sync(~0u, tid >> 5, 0), lane = tid & 31;
    const uint32_t tstart = now();
    const int rank = blockIdx.x % CL, cid = blockIdx.x / CL;
    const uint32_t bar_full = sb + OFF_FULL, bar_empty = sb + OFF_EMPTY, tk = sb + OFF_TK;
    uint4 wv[4];
    const int wrow = warp * 16 + (lane & 3) * 4;
    uint32_t b0, b1;
    auto prep_load = [&](int prb) {
        const uint32_t f0 = (prb >> 2) * 64;
        const uint16_t* const pa = p.w + ((uint32_t)(rank * 192 + wrow) * D + f0 + (lane >> 2) * 8);
#pragma unroll
        for (int j = 0; j < 4; j++) wv[j] = __ldg((const uint4*)(pa + j * D));
        b0 = __ldg(p.bias + (f0 + lane)); b1 = __ldg(p.bias + (f0 + 32 + lane));
    };
    if (!HELPER && warp < 12 && cid < 36) prep_load(cid);

    if (warp >= 12) {
        asm volatile("setmaxnreg.dec.sync.aligned.u32 32;");
        uint32_t epoch = 0;
        if (tid == NCONS + 32) asm volatile("ld.relaxed.gpu.global.u32 %0, [%1];" : "=r"(epoch) : "l"(&g_epoch) : "memory");
        if (tid == NCONS) {
#pragma unroll
            for (int s = 0; s < NSLOT; s++) { mbar_init(bar_full + 8 * s, 1); mbar_init(bar_empty + 8 * s, HELPER ? 3 : 3 * CL); }
            mbar_init(sb + OFF_MBAR, 1); mbar_init(sb + OFF_MBAR + 8, 1);
            mbar_init(sb + OFF_GO, HELPER ? 4 : 4 * CL); mbar_init(sb + OFF_GO + 8, HELPER ? 4 : 4 * CL); mbar_init(sb + OFF_GO + 16, HELPER ? 4 : 4 * CL); mbar_init(sb + OFF_EPOCH, 1);
            mbar_init(sb + OFF_FB, 1); mbar_init(sb + OFF_FB + 8, 1); mbar_init(sb + OFF_FB + 16, 1);
            asm volatile("fence.mbarrier_init.release.cluster;" ::: "memory");
            mbar_expect_tx(sb + OFF_MBAR, 36 * 4);
            if (!HELPER) asm volatile("griddepcontrol.launch_dependents;");
            asm volatile("prefetch.tensormap [%0];" :: "l"(&tmo) : "memory");
            asm volatile("prefetch.tensormap [%0];" :: "l"(&tmx) : "memory");
        }
        __syncwarp();
        if (HELPER) asm volatile("bar.sync 0;" ::: "memory");
        else asm volatile("barrier.cluster.arrive.relaxed.aligned;\nbarrier.cluster.wait.aligned;" ::: "memory");
        uint64_t pol;
        asm volatile("createpolicy.fractional.L2::evict_first.b64 %0, 1.0;" : "=l"(pol));
        if (warp == 12) {
            const int ntiles = HELPER ? p.alltiles - p.ntiles : p.ntiles;
            if (!HELPER && rank != 0) {
                auto phys = [&](int m) { return m < ntiles ? place<false>(p, m) : p.alltiles - p.nht; };
                auto prefetch = [&](int t) {
                    const int rows = min(NT, p.ntok - t * NT), r0 = rows * (rank - 1) / 2, r1 = rows * rank / 2;
                    if (lane == 0 && r1 > r0)
                        asm volatile("cp.async.bulk.prefetch.L2.global [%0], %1;" :: "l"(p.x + (size_t)t * TILE_BYTES + r0 * (D * 2)), "r"((r1 - r0) * (D * 2)) : "memory");
                };
                const int u0 = phys(p.ncl), n0 = phys(NSLOT * p.ncl) - u0;
                for (int k = cid; k < n0; k += p.ncl) { wait_until(tstart + p.pfd + k * p.pk / p.ncl); prefetch(u0 + k); }
                const int ua = phys(p.ta), n1 = phys(p.ta + p.lead1) - ua;
                for (int k = cid; k < n1; k += p.ncl) { wait_until(tstart + p.pw + (min(k, p.k1) * p.pfs + max(k - p.k1, 0) * p.pfs2) / p.ncl); prefetch(ua + k); }
            } else {
                const uint32_t rtk = HELPER ? tk : mapa(tk, lane < CL ? lane : 0), rfull = HELPER ? bar_full : mapa(bar_full, lane < CL ? lane : 0);
                int s = 0; uint32_t ph = 1, drawn = 0;
                for (int j = 0;; j++) {
                    if (j > 0 && j < NSLOT) {
#pragma unroll
                        for (int g = 0; g < 3; g++) if (blk_off(g) < OFF_X + (j + 1) * TILE_BYTES && blk_off(g) + BLK > OFF_X + j * TILE_BYTES) mbar_wait(sb + OFF_GO + 8 * g, 0);
                    }
                    mbar_wait(bar_empty + 8 * s, ph);
                    const int t = HELPER || j < NSLOT ? cid + j * p.ncl : (int)__shfl_sync(~0u, drawn, 0) + NSLOT * p.ncl;
                    const bool valid = t < ntiles;
                    if (HELPER && valid && t >= p.nha) {
                        for (int n = 0; ld32(&g_ticket) - 1 < (uint32_t)p.trig; n++) { __nanosleep(200); fail_if(n > (1 << 22)); }
                    }
                    if (valid && lane == 0) {
                        if (HELPER)
                            asm volatile("cp.async.bulk.tensor.4d.shared::cluster.global.mbarrier::complete_tx::bytes.L2::cache_hint [%0], [%1, {%3, %3, %3, %4}], [%2], %5;"
                                         :: "r"(sb + OFF_X + s * TILE_BYTES), "l"(&tmx), "r"(bar_full + 8 * s), "r"(0), "r"(place<HELPER>(p, t) * NB), "l"(pol) : "memory");
                        else
                            asm volatile("cp.async.bulk.tensor.4d.shared::cluster.global.mbarrier::complete_tx::bytes.multicast::cluster.L2::cache_hint [%0], [%1, {%3, %3, %3, %4}], [%2], %5, %6;"
                                         :: "r"(sb + OFF_X + s * TILE_BYTES), "l"(&tmx), "r"(bar_full + 8 * s), "r"(0), "r"(place<HELPER>(p, t) * NB), "h"((uint16_t)((1u << CL) - 1)), "l"(pol) : "memory");
                    }
                    if (HELPER) {
                        if (lane == 0) { sts32(tk + ((j & 7) << 2), valid ? (uint32_t)t : NO_TILE); mbar_expect_tx(bar_full + 8 * s, valid ? TILE_BYTES : 0); }
                    } else if (lane < CL) {
                        asm volatile("mbarrier.arrive.expect_tx.shared::cluster.b64 _, [%0], %1;" :: "r"(rfull + 8 * s), "r"(valid ? TILE_BYTES + 4 : 4) : "memory");
                        st_async(rtk + ((j & 7) << 2), valid ? (uint32_t)t : NO_TILE, rfull + 8 * s);
                    }
                    if (!valid) break;
                    if (!HELPER && lane == 0 && t > p.ta) {
                        auto fr = [&](int m) { const int f = m + p.leade + max(0, (p.slope1 * (p.te - m)) >> 16); return f < ntiles ? place<false>(p, f) : p.alltiles - p.nht; };
                        const int u1 = fr(t);
                        for (int u = fr(t - 1); u < u1; u++)
                            asm volatile("cp.async.bulk.prefetch.L2.global [%0], %1;" :: "l"(p.x + (size_t)u * TILE_BYTES), "r"(min(NT, p.ntok - u * NT) * (D * 2)) : "memory");
                    }
                    if (!HELPER && lane == 0 && j >= NSLOT - 1) drawn = atomicInc(&g_ticket, ntiles - p.ncl * (NSLOT - 1) - 1);
                    if (++s == NSLOT) { s = 0; ph ^= 1; }
                }
            }
        } else {
            const int g = warp - 13;
            const uint32_t rempty = HELPER ? bar_empty : mapa(bar_empty, 0);
            if (g == 0 && lane == 0) { sts32(sb + OFF_EPOCH + 8, epoch); mbar_arrive(sb + OFF_EPOCH); }
            mbar_wait(bar_full, 0);
            uint32_t t = lds32v(tk), ph = 0;
            int s = 0, nheld = 0, nout = 0, hnext = p.nh == 0 ? -1 : p.jh;
            const int nh = p.nh + (g == 0);
            uint32_t held[NH + 1];
            auto store = [&](int buf, uint32_t tile) {
                asm volatile("cp.async.bulk.tensor.2d.global.shared::cta.bulk_group.L2::cache_hint [%0, {%2, %3}], [%1], %4;"
                             :: "l"(&tmo), "r"(sb + OFF_STG + (buf * 3 + g) * STG_BYTES), "r"((g * 3 + rank) * 64), "r"((place<HELPER>(p, tile)) * NT), "l"(pol) : "memory");
            };
            auto release = [&]() {
#pragma unroll
                for (int k = 0; k <= NH; k++) if (k >= nout && k < nheld && lane == 0) store(1 + k, held[k]);
                nout = nheld;
            };
            for (int i = 0;; i++) {
                bar_sync(BAR_SFULL + g, 160);
                const int s1 = s + 1 == NSLOT ? 0 : s + 1;
                if (s1 == 0) ph ^= 1;
                if (lane == 0) { if (HELPER) mbar_arrive(bar_empty + 8 * s); else mbar_arrive_cluster(rempty + 8 * s); }
                const bool ready = __all_sync(~0u, mbar_test(bar_full + 8 * s1, ph));
                if (ready) bar_arrive(BAR_G + g, 288);
                if (lane == 0) {
                    asm volatile("fence.proxy.async.shared::cta;" ::: "memory");
                    if (i != hnext) store(0, t);
                    asm volatile("cp.async.bulk.commit_group;" ::: "memory");
                    if (g == 2 && i == 0 && atomicInc(&g_passed, p.nctas - 1) == (uint32_t)p.nctas - 1) atomicAdd(&g_epoch, 1);
                }
                __syncwarp();
                if (i == hnext) {
#pragma unroll
                    for (int k = 0; k <= NH; k++) if (k == nheld) held[k] = t;
                    hnext = ++nheld < nh ? hnext + p.jd : -1;
                }
                s = s1;
                if (!ready) { mbar_wait(bar_full + 8 * s, ph); bar_arrive(BAR_G + g, 288); }
                t = lds32v(tk + (((i + 1) & 7) << 2));
                if (t >= (uint32_t)p.rel && nout < nheld) { release(); if (lane == 0) asm volatile("cp.async.bulk.commit_group;" ::: "memory"); }
                if (lane == 0) asm volatile("cp.async.bulk.wait_group.read 0;" ::: "memory");
                __syncwarp();
                if (t == NO_TILE) break;
                bar_arrive(BAR_SEMPTY + g, 160);
            }
        }
        __syncwarp();
        if (!HELPER) asm volatile("barrier.cluster.arrive.relaxed.aligned;\nbarrier.cluster.wait.aligned;" ::: "memory");
    } else {
        asm volatile("setmaxnreg.inc.sync.aligned.u32 160;");
        const int wg = warp >> 2, r = lane >> 2, q = lane & 3;
        uint32_t epoch;
        if (HELPER) asm volatile("bar.sync 0;" ::: "memory");
        else {
            int prb = cid;
            asm volatile("barrier.cluster.arrive.relaxed.aligned;" ::: "memory");
            if (prb >= 36) asm volatile("barrier.cluster.wait.aligned;" ::: "memory");
#pragma unroll 1
            for (int round = 0; prb < 36; prb += p.ncl, round++) {
                const uint32_t wsm = sb + OFF_WST, msk = sb + OFF_MSK + (round & 1) * 144, mbar = sb + OFF_MBAR + (round & 1) * 8;
                if (round) {
                    bar_sync(3, 384);
                    if (tid == 0) mbar_expect_tx(mbar, 36 * 4);
                    prep_load(prb);
                }
                const uint32_t tk2 = min2(min2(tie_key(wv[0].x, wv[1].x, wv[2].x, wv[3].x), tie_key(wv[0].y, wv[1].y, wv[2].y, wv[3].y)),
                                          min2(tie_key(wv[0].z, wv[1].z, wv[2].z, wv[3].z), tie_key(wv[0].w, wv[1].w, wv[2].w, wv[3].w)));
                const uint32_t mk = __ballot_sync(~0u, (tk2 & 0xFFFFu) == 0 || tk2 < 0x10000u);
                if (round == 0) asm volatile("barrier.cluster.wait.aligned;" ::: "memory");
                if (lane < CL) st_async(mapa(msk + (rank * 12 + warp) * 4, lane), mk, mapa(mbar, lane));
#pragma unroll
                for (int j = 0; j < 4; j++) {
                    const int row = wrow + j;
                    const uint32_t ad = wsm + row * 128 + (((lane >> 2) ^ ((row & 1) | ((row >> 1) & 6))) << 4);
                    asm volatile("st.shared.v4.b32 [%0], {%1,%2,%3,%4};" :: "r"(ad), "r"(wv[j].x), "r"(wv[j].y), "r"(wv[j].z), "r"(wv[j].w) : "memory");
                }
                if (warp >= 6) bar_arrive(1, 384);
                else {
                    bar_sync(1, 384);
                    mbar_wait(sb + OFF_EPOCH, 0);
                    epoch = lds32v(sb + OFF_EPOCH + 8);
                    uint8_t* const scr = (uint8_t*)p.scr + (epoch & 1) * SCR_END;
                    mbar_wait(mbar, (round >> 1) & 1);
                    uint32_t m0 = 0, m1 = 0;
                    if (lane < KSTEPS) asm volatile("ld.volatile.shared.v2.b32 {%0,%1}, [%2];" : "=r"(m0), "=r"(m1) : "r"(msk + 8 * lane) : "memory");
                    uint32_t c0 = m0 - ((m0 >> 1) & 0x55555555u), c1 = m1 - ((m1 >> 1) & 0x55555555u);
                    c0 = (c0 & 0x33333333u) + ((c0 >> 2) & 0x33333333u) + (c1 & 0x33333333u) + ((c1 >> 2) & 0x33333333u);
                    c1 = __reduce_add_sync(~0u, (c0 >> 4) & 0x0F0F0F0Fu); c0 = __reduce_add_sync(~0u, c0 & 0x0F0F0F0Fu);
                    auto key = [&](int v) { return ((((v & 1) ? c1 : c0) >> (4 * (v & 6))) & 0xFFu) * 8 + v; };
                    const uint32_t ku = key(lane & 7);
                    const uint32_t l0 = __ballot_sync(~0u, key(lane >> 3) < ku), l1 = __ballot_sync(~0u, key(4 + (lane >> 3)) < ku);
                    const int rk = __popc((l0 >> (lane & 7)) & 0x01010101u) + __popc((l1 >> (lane & 7)) & 0x01010101u);
                    const int pp = prb & 3;
                    const int ulo = __ffs(__ballot_sync(~0u, rk == pp)) - 1, uhi = __ffs(__ballot_sync(~0u, rk == 7 - pp)) - 1;
                    uint32_t lo[4], hi[4];
                    load_unit(wsm, warp, ulo, lane, lo); load_unit(wsm, warp, uhi, lane, hi);
                    const uint32_t mm = (((m0 >> (4 * ulo)) | (m0 >> (4 * uhi))) & 15u) | ((((m1 >> (4 * ulo)) | (m1 >> (4 * uhi))) & 15u) << 4);
                    const uint2 bias2 = make_uint2(__shfl_sync(~0u, ulo < 4 ? b0 : b1, (ulo * 8 + r) & 31) * 0x10001u, __shfl_sync(~0u, uhi < 4 ? b0 : b1, (uhi * 8 + r) & 31) * 0x10001u);
                    emit_step(lo, hi, mm, prb, rank * 6 + warp, lane, ulo | (uhi << 4), bias2, scr, p.over, epoch + 1);
                }
            }
            if (cid >= 36 || warp >= 6) { mbar_wait(sb + OFF_EPOCH, 0); epoch = lds32v(sb + OFF_EPOCH + 8); }
            if (warp >= 6) for (int i = blockIdx.x * 192 + tid - 192; i < SCR_END / 16; i += gridDim.x * 192) p.scr[(~epoch & 1) * (SCR_END / 16) + i] = make_uint4(0, 0, 0, 0);
        }
        if (HELPER) { mbar_wait(sb + OFF_EPOCH, 0); epoch = lds32v(sb + OFF_EPOCH + 8); }
        if (wg == 2) bar_arrive(BAR_T, 256);
        const int mt = wg * 3 + rank, rb = mt * 4 + (warp & 3);
        const uint8_t* const scr = (const uint8_t*)p.scr + (epoch & 1) * SCR_END + mt * BLK;
        const int fo = (warp & 3) * 512 + lane * 16, io = BLK_I + (warp & 3) * 128 + r * 16, sl = (r >> 1) * 8 + q * 2 + (r & 1), so = BLK_S + (warp & 3) * 2560 + sl * 16;
        const int mo = BLK_M + ((warp & 3) * KSTEPS + (q >> 1)) * 64 + r * 8 + (q & 1) * 4;
        if (!HELPER && cid < 36) bar_sync(2, 384);
        const uint32_t blk = sb + blk_off(wg);
        if (warp == 0) {
            if (HELPER || cid >= 36 || p.ncl < 36) for (int n = 0; __any_sync(~0u, ld32(scr + 17 * 2048 + fo) == 0); n++) fail_if(n > (1 << 22));
            if (lane < 3) {
                mbar_expect_tx(sb + OFF_FB + 8 * lane, BLK);
                asm volatile("cp.async.bulk.shared::cluster.global.mbarrier::complete_tx::bytes [%0], [%1], %2, [%3];"
                             :: "r"(sb + blk_off(lane)), "l"(scr + lane * 3 * BLK), "r"(BLK), "r"(sb + OFF_FB + 8 * lane) : "memory");
            }
        }
        uint32_t a[KSTEPS][4], meta[9];
        uint2 rv[5]; uint32_t ro[5];
        uint32_t info, bias_lo, bias_hi;
        {
            const uint8_t* const fp = scr + fo; const uint8_t* const ip = scr + io; const uint8_t* const sp = scr + so; const uint8_t* const mp = scr + mo;
            mbar_wait(sb + OFF_FB + 8 * wg, 0);
            uint4 i0 = lds128(blk + io), sv[5];
#pragma unroll
            for (int j = 0; j < 5; j++) sv[j] = lds128(blk + so + j * 512);
#pragma unroll
            for (int j = 0; j < 9; j++) meta[j] = lds32(blk + mo + j * 128);
#pragma unroll
            for (int k = 0; k < KSTEPS; k++) { const uint4 v = lds128(blk + fo + k * 2048); a[k][0] = v.x; a[k][1] = v.y; a[k][2] = v.z; a[k][3] = v.w; }
            for (int n = 0;; n++) {
                uint32_t lo = __vimin3_u32(__vimin3_u32(i0.x, meta[8], sv[0].z), sv[1].z, __vimin3_u32(sv[2].z, sv[3].z, sv[4].z));
#pragma unroll
                for (int j = 0; j < 8; j += 2) lo = __vimin3_u32(lo, meta[j], meta[j + 1]);
#pragma unroll
                for (int k = 0; k < KSTEPS; k += 2) lo = __vimin3_u32(lo, a[k][0], a[k + 1][0]);
                if (__all_sync(~0u, lo != 0)) break;
                fail_if(n > (1 << 20));
                ld128_if(i0.x == 0, ip, i0.x, i0.y, i0.z, i0.w);
#pragma unroll
                for (int j = 0; j < 5; j++) ld128_if(sv[j].z == 0, sp + j * 512, sv[j].x, sv[j].y, sv[j].z, sv[j].w);
#pragma unroll
                for (int j = 0; j < 9; j++) ld32_if(meta[j] == 0, mp + j * 128, meta[j]);
#pragma unroll
                for (int k = 0; k < KSTEPS; k++) ld128_if(a[k][0] == 0, fp + k * 2048, a[k][0], a[k][1], a[k][2], a[k][3]);
            }
            info = i0.x; bias_lo = i0.y; bias_hi = i0.z;
#pragma unroll
            for (int j = 0; j < 5; j++) { rv[j] = make_uint2(sv[j].x, sv[j].y); ro[j] = sv[j].z; }
        }
#pragma unroll
        for (int j = 0; j < 4; j++) { rv[j].x ^= p.zero; rv[j].y ^= p.zero; }
        if ((wg || !BLK_FITS) && lane == 0) { if (HELPER) mbar_arrive(sb + OFF_GO + 8 * wg); else mbar_arrive_cluster(mapa(sb + OFF_GO + 8 * wg, 0)); }
        info = __shfl_sync(~0u, info, 0);
        const int ngrp = info & 0xFF, ulo = (info >> 8) & 7, uhi = (info >> 12) & 7;
#pragma unroll 1
        for (int j = 5; j < ngrp; j++)
            for (int n = 0; __any_sync(~0u, ld128(p.over + (rb * 36 + j) * 32 + sl).w != epoch + 1); n++) fail_if(n > (1 << 20));
        mbar_wait(bar_full, 0);
        const uint32_t stg = sb + OFF_STG + wg * STG_BYTES + ((lane >> 4) * 8 + (lane & 7)) * 128 + (((((lane >> 3) & 1) ? uhi : ulo) ^ (lane & 7)) << 4);
        float acc[NACC];
        uint32_t bq[NB][2], b4[NB];
        auto gather = [&](uint32_t xb) {
#pragma unroll
            for (int j = 0; j < 3; j++)
#pragma unroll
                for (int n = 0; n < NB; n++) { const uint32_t v = lds32(xb + ro[j] + (n * 9216 - RO_BIAS)); if (j < 2) acc[4 * n + j] = __uint_as_float(v); else bq[n][0] = v; }
            if (ngrp > 3) {
#pragma unroll
                for (int n = 0; n < NB; n++) bq[n][1] = lds32(xb + ro[3] + (n * 9216 - RO_BIAS));
                if (ngrp > 4) {
#pragma unroll
                    for (int n = 0; n < NB; n++) b4[n] = lds32(xb + ro[4] + (n * 9216 - RO_BIAS));
                }
            }
        };
        const int me = tid >> 7, nxt = __shfl_sync(~0u, BAR_T + (me == 2 ? 0 : me + 1), 0), prv = __shfl_sync(~0u, BAR_G + (me == 0 ? 2 : me - 1), 0);
#pragma unroll
        for (int n = 0; n < NB; n++) b4[n] = bq[n][1] = 0;
        gather(sb + OFF_X);
        bar_sync(BAR_T + wg, 256);
        auto bdesc = [](uint32_t x) { return ((uint64_t)1 << 62) | ((uint64_t)(9216 >> 4) << 32) | ((uint64_t)1 << 16) | (uint64_t)(x >> 4); };
        uint32_t xb = sb + OFF_X;
        uint64_t desc = bdesc(xb);
        int hnext = p.nh == 0 ? -1 : p.jh, hbuf = 3 * STG_BYTES;
        bool more = true;
        for (int i = 0; more; i++) {
            auto rows03 = [&]() {
#pragma unroll
                for (int n = 0; n < NB; n++) mma_k16(acc + 4 * n, rv[0], rv[1], __float_as_uint(acc[4 * n]), __float_as_uint(acc[4 * n + 1]), 0.f, 0.f, 0.f, 0.f);
#pragma unroll
                for (int n = 0; n < NB; n++) mma_k16(acc + 4 * n, rv[2], rv[3], bq[n][0], bq[n][1], acc[4 * n], acc[4 * n + 1], acc[4 * n + 2], acc[4 * n + 3]);
            };
            if (ngrp <= 4) rows03();
            else {
                rows03();
#pragma unroll
                for (int n = 0; n < NB; n++) mma_k8(acc + 4 * n, rv[4], b4[n]);
#pragma unroll 1
                for (int j = 5; j < ngrp; j++) {
                    const uint4 o = __ldca(p.over + (rb * 36 + j) * 32 + sl);
#pragma unroll
                    for (int n = 0; n < NB; n++) b4[n] = lds32(xb + o.z + (n * 9216 - RO_BIAS));
#pragma unroll
                    for (int n = 0; n < NB; n++) mma_k8(acc + 4 * n, make_uint2(o.x, o.y), b4[n]);
                }
            }
            asm volatile("wgmma.fence.sync.aligned;" ::: "memory");
#pragma unroll
            for (int k = 0; k < KSTEPS; k++) {
                const uint64_t d = desc + (uint64_t)(((k >> 1) * 1024 + (k & 1) * 64) >> 4);
                if (k & 1) wgmma_sp<1>(acc, a[k], d, meta[k >> 1]);
                else       wgmma_sp<0>(acc, a[k], d, meta[k >> 1]);
                if (k == SPLIT - 1) asm volatile("wgmma.commit_group.sync.aligned;" ::: "memory");
            }
            asm volatile("wgmma.commit_group.sync.aligned;" ::: "memory");
            bar_arrive(nxt, 256);
            xb = xb == sb + OFF_X + (NSLOT - 1) * TILE_BYTES ? sb + OFF_X : xb + TILE_BYTES;
            desc = bdesc(xb);
            uint32_t sq = stg;
            if (i == hnext) { sq += hbuf; hbuf += 3 * STG_BYTES; hnext = hbuf <= (p.nh + (wg == 0)) * 3 * STG_BYTES ? hnext + p.jd : -1; }
            asm volatile("wgmma.wait_group.sync.aligned 1;" ::: "memory");
            if (wg != 0 || i != 0) bar_arrive(prv, 288);
            if (i != 0) bar_sync(BAR_SEMPTY + me, 160);
            asm volatile("wgmma.wait_group.sync.aligned 0;" ::: "memory");
#pragma unroll
            for (int n = 0; n + 1 < NB; n += 2) {
                const uint32_t p0 = pack_bias(acc[4 * n], acc[4 * n + 1], bias_lo), p1 = pack_bias(acc[4 * n + 2], acc[4 * n + 3], bias_hi);
                const uint32_t p2 = pack_bias(acc[4 * n + 4], acc[4 * n + 5], bias_lo), p3 = pack_bias(acc[4 * n + 6], acc[4 * n + 7], bias_hi);
                asm volatile("stmatrix.sync.aligned.m8n8.x4.trans.shared.b16 [%0], {%1,%2,%3,%4};" :: "r"(sq + n * 1024), "r"(p0), "r"(p1), "r"(p2), "r"(p3) : "memory");
            }
            if (NB & 1) {
                const uint32_t p0 = pack_bias(acc[NACC - 4], acc[NACC - 3], bias_lo), p1 = pack_bias(acc[NACC - 2], acc[NACC - 1], bias_hi);
                asm volatile("stmatrix.sync.aligned.m8n8.x2.trans.shared.b16 [%0], {%1,%2};" :: "r"(sq + (NB - 1) * 1024), "r"(p0), "r"(p1) : "memory");
            }
            bar_arrive(BAR_SFULL + me, 160);
            bar_sync(BAR_G + me, 288);
            const uint32_t tn = lds32v(tk + (((i + 1) & 7) << 2));
            gather(xb);
            more = __any_sync(~0u, tn != NO_TILE);
            if (more || wg == 0) bar_sync(BAR_T + me, 256);
        }
        if (wg == 0) bar_arrive(BAR_G + 2, 288);
        __syncwarp();
        if (!HELPER) asm volatile("barrier.cluster.arrive.relaxed.aligned;\nbarrier.cluster.wait.aligned;" ::: "memory");
    }
}

typedef CUresult (*EncodeFn)(CUtensorMap*, CUtensorMapDataType, cuuint32_t, void*, const cuuint64_t*, const cuuint64_t*, const cuuint32_t*, const cuuint32_t*,
                             CUtensorMapInterleave, CUtensorMapSwizzle, CUtensorMapL2promotion, CUtensorMapFloatOOBfill);

extern "C" void kernel_launch(void* const* d_in, const int* in_sizes, int n_in, void* d_out, int out_size) {
    static EncodeFn enc = nullptr;
    static int ncl = 0, nhelp = 0;
    const int ntok = in_sizes[0] / D;
    cudaLaunchConfig_t cfg = {};
    cudaLaunchAttribute at[1];
    at[0].id = cudaLaunchAttributeClusterDimension; at[0].val.clusterDim.x = CL; at[0].val.clusterDim.y = 1; at[0].val.clusterDim.z = 1;
    cfg.blockDim = dim3(NTHREADS); cfg.dynamicSmemBytes = SMEM_BYTES; cfg.attrs = at; cfg.numAttrs = 1; cfg.stream = cudaStreamPerThread;
    if (!enc) {
        cudaDriverEntryPointQueryResult qr; void* fn = nullptr;
        cudaGetDriverEntryPoint("cuTensorMapEncodeTiled", &fn, cudaEnableDefault, &qr);
        enc = (EncodeFn)fn;
        cudaFuncSetAttribute(spgemm_kernel<false>, cudaFuncAttributeMaxDynamicSharedMemorySize, SMEM_BYTES);
        cudaFuncSetAttribute(spgemm_kernel<true>, cudaFuncAttributeMaxDynamicSharedMemorySize, SMEM_BYTES);
        int dev = 0, nsm = 0;
        cudaGetDevice(&dev);
        cudaDeviceGetAttribute(&nsm, cudaDevAttrMultiProcessorCount, dev);
        cfg.gridDim = dim3(CL * (nsm / CL));
        cudaOccupancyMaxActiveClusters(&ncl, spgemm_kernel<false>, &cfg);
        if (ncl < 1) ncl = 1;
        nhelp = nsm > CL * ncl ? (nsm - CL * ncl) / CL : 0;
    }
    CUtensorMap tmx, tmo;
    {
        cuuint64_t dims[4] = {64, 8, 9, (cuuint64_t)(ntok / 8)};
        cuuint64_t strides[3] = {D * 2, 128, 8 * D * 2};
        cuuint32_t box[4] = {64, 8, 9, NB}, es[4] = {1, 1, 1, 1};
        enc(&tmx, CU_TENSOR_MAP_DATA_TYPE_BFLOAT16, 4, d_in[0], dims, strides, box, es, CU_TENSOR_MAP_INTERLEAVE_NONE,
            CU_TENSOR_MAP_SWIZZLE_128B, CU_TENSOR_MAP_L2_PROMOTION_L2_128B, CU_TENSOR_MAP_FLOAT_OOB_FILL_NONE);
    }
    {
        cuuint64_t dims[2] = {D, (cuuint64_t)ntok};
        cuuint64_t strides[1] = {D * 2};
        cuuint32_t box[2] = {64, NT}, es[2] = {1, 1};
        enc(&tmo, CU_TENSOR_MAP_DATA_TYPE_BFLOAT16, 2, d_out, dims, strides, box, es, CU_TENSOR_MAP_INTERLEAVE_NONE,
            CU_TENSOR_MAP_SWIZZLE_128B, CU_TENSOR_MAP_L2_PROMOTION_NONE, CU_TENSOR_MAP_FLOAT_OOB_FILL_NONE);
    }
    Params p;
    p.w = (const uint16_t*)d_in[1]; p.bias = (const uint16_t*)d_in[2]; p.x = (const uint8_t*)d_in[0];
    p.ntok = ntok;
    cudaGetSymbolAddress((void**)&p.scr, g_scr); cudaGetSymbolAddress((void**)&p.over, g_over);
    p.zero = 0;
    p.alltiles = (ntok + NT - 1) / NT;
    const int nc = ncl < p.alltiles ? ncl : p.alltiles;
    p.a = nhelp ? (int)(2 * nc / (nhelp * 1.07) + 0.5) : 2;
    if (p.a < 2) p.a = 2;
    const int nblk = (int)(p.alltiles / (p.a + 2) * 0.65);
    const int nh = nhelp && 2 * nblk >= nhelp && p.alltiles - 2 * nblk >= nc ? nhelp : 0;
    p.nha = nh ? 2 * nblk : 0; p.nht = p.alltiles > 16 * nc ? nh : 0;
    p.ntiles = p.alltiles - p.nha - p.nht;
    p.trig = p.ntiles - nc * NSLOT - 30;
    p.nfull = nh ? nblk * p.a : 0; p.amagic = (int)(0xFFFFFFFFu / (uint32_t)p.a + 1);
    p.ncl = nc; p.nctas = CL * (nc + nh);
    p.nh = (int)NH; p.jh = 4; p.jd = 4; p.rel = p.ntiles - 50;
    auto tiles = [](double v) { return (int)(v * 56 / NT); };
    auto ns = [](double v) { return (int)(v * NT / 56); };
    p.pfd = 1500; p.pk = ns(900);
    p.ta = (int)(p.ntiles * 0.4) + 1; p.lead1 = tiles(250); p.pw = 3000;
    p.k1 = tiles(68); p.pfs = ns(700); p.pfs2 = ns(2300);
    p.te = p.ntiles + 2; p.leade = tiles(50); p.slope1 = ((p.lead1 - p.leade) << 16) / (p.te - p.ta);
    cfg.gridDim = dim3(CL * nc);
    cudaLaunchKernelEx(&cfg, spgemm_kernel<false>, tmx, tmo, p);
    if (nh) {
        at[0].id = cudaLaunchAttributeProgrammaticStreamSerialization; at[0].val.programmaticStreamSerializationAllowed = 1;
        cfg.gridDim = dim3(CL * nh);
        p.ncl = nh;
        p.nh = p.nht ? NH : 0; p.jh = p.nha / nh - 10; p.jd = 1; p.rel = p.nha;
        cudaLaunchKernelEx(&cfg, spgemm_kernel<true>, tmx, tmo, p);
    }
}
```

```cpp
#include <cuda_runtime.h>
#include <cuda_bf16.h>
#include <cuda.h>
#include <stdint.h>

constexpr int D = 576;
constexpr int NH = 2;
constexpr int NT = 48;
constexpr int NSLOT = 3;
constexpr int SPLIT = 13;
constexpr int KSTEPS = 18;
constexpr int CL = 3;
constexpr int TILE_BYTES = NT * D * 2;
constexpr int STG_BYTES = NT * 128;
constexpr int NACC = NT / 2;
constexpr int NB = NT / 8;
constexpr int NCONS = 384;
constexpr int NTHREADS = 512;
constexpr uint32_t NO_TILE = 0xFFFFFFFFu;

constexpr int OFF_X = 0;
constexpr int OFF_STG = OFF_X + NSLOT * TILE_BYTES;
constexpr int OFF_WST = OFF_STG;
constexpr int OFF_FULL = OFF_STG + ((1 + NH) * 3 + 1) * STG_BYTES;
constexpr int OFF_EMPTY = OFF_FULL + 8 * NSLOT;
constexpr int OFF_MBAR = OFF_EMPTY + 8 * NSLOT;
constexpr int OFF_GO = OFF_MBAR + 16;
constexpr int OFF_FB = OFF_GO + 24;
constexpr int OFF_EPOCH = OFF_FB + 24;
constexpr int OFF_TK = OFF_EPOCH + 16;
constexpr int OFF_MSK = OFF_TK + 32;
constexpr int SMEM_BYTES = OFF_MSK + 2 * 36 * 4 + 1024;
static_assert(SMEM_BYTES <= 232448 && NSLOT < 8 && NSLOT >= 3, "layout");
constexpr int BAR_T = 4, BAR_SFULL = 7, BAR_SEMPTY = 10, BAR_G = 13;

constexpr int BLK_M = KSTEPS * 2048, BLK_S = BLK_M + 4 * KSTEPS * 64, BLK_I = BLK_S + 4 * 2560, BLK = BLK_I + 4 * 128, SCR_END = 9 * BLK;
constexpr bool BLK_FITS = BLK <= TILE_BYTES && BLK <= OFF_FULL - OFF_STG;
__host__ __device__ constexpr int blk_off(int g) { return BLK_FITS ? (g == 0 ? OFF_STG : OFF_X + g * TILE_BYTES) : OFF_X + TILE_BYTES + (g + 2) % 3 * BLK; }
static_assert(blk_off(0) + BLK <= OFF_FULL && blk_off(2) + BLK <= OFF_STG && OFF_WST + 192 * 128 <= OFF_FULL, "fragment blocks");
__device__ __align__(128) uint4    g_scr[2][SCR_END / 16];
__device__ __align__(128) uint4    g_over[36 * 144 * 8];
__device__ __align__(128) uint32_t g_epoch;
__device__ __align__(128) uint32_t g_passed;
__device__ __align__(128) uint32_t g_ticket;

__device__ __forceinline__ uint32_t now() { uint32_t c; asm volatile("mov.u32 %0, %%globaltimer_lo;" : "=r"(c)); return c; }
__device__ __forceinline__ void wait_until(uint32_t due) { while ((int)(now() - due) < 0) __nanosleep(20); }

__device__ __forceinline__ uint32_t max2(uint32_t a, uint32_t b) { uint32_t d; asm("max.u16x2 %0, %1, %2;" : "=r"(d) : "r"(a), "r"(b)); return d; }
__device__ __forceinline__ uint32_t min2(uint32_t a, uint32_t b) { uint32_t d; asm("min.u16x2 %0, %1, %2;" : "=r"(d) : "r"(a), "r"(b)); return d; }
__device__ __forceinline__ uint32_t sign2(uint32_t a) { uint32_t d; asm("prmt.b32 %0, %1, %1, 0xBB99;" : "=r"(d) : "r"(a)); return d; }
__device__ __forceinline__ void zip4(uint32_t a01, uint32_t a23, uint32_t b01, uint32_t b23, uint32_t (&x)[4]) {
    x[0] = __byte_perm(a01, b01, 0x5410); x[1] = __byte_perm(a01, b01, 0x7632); x[2] = __byte_perm(a23, b23, 0x5410); x[3] = __byte_perm(a23, b23, 0x7632);
}
__device__ __forceinline__ void middle2(const uint32_t (&x)[4], uint32_t (&m)[4], uint32_t& u, uint32_t& v) {
#pragma unroll
    for (int i = 0; i < 4; i++) m[i] = x[i] & 0x7FFF7FFFu;
    u = min2(max2(m[0], m[1]), max2(m[2], m[3])); v = max2(min2(m[0], m[1]), min2(m[2], m[3]));
}
__device__ __forceinline__ uint32_t tie_key(uint32_t x0, uint32_t x1, uint32_t x2, uint32_t x3) {
    const uint32_t x[4] = {x0, x1, x2, x3};
    uint32_t m[4], u, v;
    middle2(x, m, u, v);
    return max2(u, 0x00010001u) ^ v;
}
__device__ __forceinline__ void load_unit(uint32_t wsm, int ls, int unit, int lane, uint32_t (&m)[4]) {
    const int row = ls * 32 + (lane >> 4) * 16 + ((lane & 7) >> 1) * 4 + ((lane >> 3) & 1) * 2 + (lane & 1);
    const uint32_t ad = wsm + row * 128 + ((unit ^ ((row & 1) | ((row >> 1) & 6))) << 4);
    asm volatile("ldmatrix.sync.aligned.m8n8.x4.trans.shared.b16 {%0,%1,%2,%3}, [%4];" : "=r"(m[0]), "=r"(m[1]), "=r"(m[2]), "=r"(m[3]) : "r"(ad) : "memory");
}
__device__ __forceinline__ void split_pair(const uint32_t (&x)[4], bool P, uint32_t& alo, uint32_t& ahi, uint32_t& nib, uint32_t& rlo, uint32_t& rhi) {
    uint32_t m[4], u, v;
    middle2(x, m, u, v);
    const uint32_t c = 0x80008000u - max2(max2(u, v), 0x00010001u);
    uint32_t k0 = sign2(m[0] + c), k1 = sign2(m[1] + c), k2 = sign2(m[2] + c), k3 = sign2(m[3] + c);
    const uint32_t three = (k0 & k1 & (k2 | k3)) | (k2 & k3 & (k0 | k1)), four = k0 & k1 & k2 & k3;
    const uint32_t pa = P ? k2 : k0, pb = P ? k3 : k1;
    const uint32_t ra = three & pa, rb = three & pb & (four | ~pa);
    const uint32_t va = (P ? x[2] : x[0]) & ra, vb = (P ? x[3] : x[1]) & rb;
    if (P) { k2 &= ~ra; k3 &= ~rb; } else { k0 &= ~ra; k1 &= ~rb; }
    const uint32_t s1 = k1 & k0, s2 = k2 & (k0 | k1);
    const uint32_t t = (k1 & x[1]) | (~k1 & k2 & x[2]);
    const uint32_t x0 = (k0 & x[0]) | (~k0 & t), x1 = (s1 & x[1]) | (s2 & x[2]) | (k3 & x[3]);
    nib = (~k0 & k1 & 0x00010001u) | (~k0 & ~k1 & 0x00020002u) | (~s2 & 0x00040004u) | (~s1 & 0x00080008u);
    alo = __byte_perm(x0, x1, 0x5410); ahi = __byte_perm(x0, x1, 0x7632);
    rlo = __byte_perm(va, vb, 0x5410); rhi = __byte_perm(va, vb, 0x7632);
}
__device__ __forceinline__ uint32_t nonzero(uint32_t v) { return v ? v : 0x8000u; }
__device__ __forceinline__ void pub32(void* a, uint32_t v) { asm volatile("st.relaxed.gpu.global.u32 [%0], %1;" :: "l"(a), "r"(v) : "memory"); }
__device__ __forceinline__ void pub128(bool c, void* a, uint32_t x, uint32_t y, uint32_t z, uint32_t w) {
    asm volatile("{\n.reg .pred p;\n.reg .b64 s, t;\n.reg .b128 v;\nsetp.ne.u32 p, %5, 0;\nmov.b64 s, {%1, %2};\nmov.b64 t, {%3, %4};\nmov.b128 v, {s, t};\n@p st.relaxed.gpu.global.b128 [%0], v;\n}\n"
                 :: "l"(a), "r"(x), "r"(y), "r"(z), "r"(w), "r"((uint32_t)c) : "memory");
}
constexpr int RO_BIAS = 16;
__device__ __forceinline__ uint32_t resid_off(int g, int P, int r) {
    int k0 = 4 * g + 2 * P;
    int chunk = k0 >> 6, byte = (k0 & 63) * 2;
    return chunk * 1024 + r * 128 + (((byte >> 4) ^ r) << 4) + (byte & 15);
}
__device__ __forceinline__ void emit_step(const uint32_t (&lo)[4], const uint32_t (&hi)[4], uint32_t mm, int rb, int ks, int lane, uint32_t units, uint2 bias2,
                                          uint8_t* scr, uint4* over, uint32_t tag) {
    scr += (rb >> 2) * BLK;
    const int wp = rb & 3;
    const int lo16 = (lane >> 3) * 128 + ((lane >> 2) & 1) * 16;
    uint8_t* const s0 = scr + BLK_S + wp * 2560 + lo16;
    uint8_t* const s1 = (uint8_t*)(over + rb * 144 * 8) + lo16;
    auto put_slot = [&](bool c, int sl, uint32_t v0, uint32_t v1, uint32_t off) {
        pub128(c, (sl < 20 ? s0 : s1) + (sl >> 2) * 512 + (sl & 3) * 32, v0, v1, off + RO_BIAS, tag);
    };
    const int r = lane >> 2, q = lane & 3, g0 = ks * 8 + q, g1 = g0 + 4;
    const uint32_t gm = __shfl_sync(~0u, mm, ks);
    const uint32_t c2 = __popc(mm & 0x55u) | (__popc(mm & 0xAAu) << 16);
    const uint32_t tot = __reduce_add_sync(~0u, c2), pre = __reduce_add_sync(~0u, lane < ks ? c2 : 0u);
    const int ne = tot & 0xFFFF, no = tot >> 16;
    const uint32_t par = (q & 1) ? 0xAAu : 0x55u;
    const int base = (q & 1) ? pre >> 16 : pre & 0xFFFF;
    const int rk0 = base + __popc(gm & par & ((1u << q) - 1)), rk1 = base + __popc(gm & par & ((16u << q) - 1));
    uint32_t a[4], rs[4], x[4], w0, w1;
    zip4(lo[0], lo[1], hi[0], hi[1], x); split_pair(x, rk0 & 1, a[0], a[1], w0, rs[0], rs[1]);
    zip4(lo[2], lo[3], hi[2], hi[3], x); split_pair(x, rk1 & 1, a[2], a[3], w1, rs[2], rs[3]);
    pub128(true, scr + ks * 2048 + wp * 512 + lane * 16, nonzero(a[0]), a[1], a[2], a[3]);
    w0 <<= 4 * q; w1 <<= 4 * q;
    w0 |= __shfl_xor_sync(~0u, w0, 1); w1 |= __shfl_xor_sync(~0u, w1, 1);
    w0 |= __shfl_xor_sync(~0u, w0, 2); w1 |= __shfl_xor_sync(~0u, w1, 2);
    if (q < 2) pub32(scr + BLK_M + (wp * KSTEPS + ks) * 64 + r * 8 + q * 4, q ? w1 : w0);
    const int em = min(ne, max(8, 16 - no)), om = min(no, 16 - em);
    const int odd = q & 1, m = odd ? om : em;
#pragma unroll
    for (int e = 0; e < 2; e++) {
        const int rk = e ? rk1 : rk0, t = 15 - rk;
        const int u = min(rk, t), in = (u >> 1) * 4 + (u & 1) + 2 * (odd ^ (rk >> 3 & 1)), out = 16 + (odd ? ne - em : 0) + rk - m;
        const int sl = rk >= m ? out : in;
        put_slot((gm >> (4 * e + q)) & 1, sl, rs[2 * e], rs[2 * e + 1], resid_off(e ? g1 : g0, rk & 1, r));
    }
    const int ntot = ne + no;
    const int ng = ntot > 16 ? (ntot + 3) >> 2 : min(4, (max(ne, no) + 1) >> 1);
    pub128(ks == 7 && q == 0, scr + BLK_I + wp * 128 + r * 16, ng | (units << 8), bias2.x, bias2.y, 0);
    const int idx = 2 * ks + (q & 1);
    const int frow = ks < 5 ? ks : ng - 1;
    const bool fill = ks < 4 ? !(idx < ((q >> 1) ? om : em) || (15 - idx) < ((q >> 1) ? em : om)) : (ks == 4 || (ks == 5 && ng > 5)) && 4 * frow + q >= ntot;
    put_slot(fill, frow * 4 + q, 0, 0, resid_off(q >> 1, q & 1, r));
}

template<int SEL> __device__ __forceinline__ void wgmma_sp(float (&d)[NACC], const uint32_t (&a)[4], uint64_t bdesc, uint32_t meta) {
    asm volatile("wgmma.mma_async.sp.sync.aligned.m64n48k32.f32.bf16.bf16 {%0, %1, %2, %3, %4, %5, %6, %7, %8, %9, %10, %11, %12, %13, %14, %15, %16, %17, %18, %19, %20, %21, %22, %23}, {%24, %25, %26, %27}, %28, %29, %30, 1, 1, 1, 0;"
        : "+f"(d[0]), "+f"(d[1]), "+f"(d[2]), "+f"(d[3]), "+f"(d[4]), "+f"(d[5]), "+f"(d[6]), "+f"(d[7]), "+f"(d[8]), "+f"(d[9]), "+f"(d[10]), "+f"(d[11]), "+f"(d[12]), "+f"(d[13]), "+f"(d[14]), "+f"(d[15]), "+f"(d[16]), "+f"(d[17]), "+f"(d[18]), "+f"(d[19]), "+f"(d[20]), "+f"(d[21]), "+f"(d[22]), "+f"(d[23])
        : "r"(a[0]), "r"(a[1]), "r"(a[2]), "r"(a[3]), "l"(bdesc), "r"(meta), "n"(SEL));
}
__device__ __forceinline__ void bar_sync(int id, int n) { asm volatile("bar.sync %0, %1;" :: "r"(id), "r"(n) : "memory"); }
__device__ __forceinline__ void bar_arrive(int id, int n) { asm volatile("bar.arrive %0, %1;" :: "r"(id), "r"(n) : "memory"); }

__device__ __forceinline__ void mbar_init(uint32_t bar, uint32_t cnt) { asm volatile("mbarrier.init.shared::cta.b64 [%0], %1;" :: "r"(bar), "r"(cnt) : "memory"); }
__device__ __forceinline__ void mbar_expect_tx(uint32_t bar, uint32_t bytes) {
    asm volatile("mbarrier.arrive.expect_tx.shared::cta.b64 _, [%0], %1;" :: "r"(bar), "r"(bytes) : "memory");
}
__device__ __forceinline__ void mbar_arrive(uint32_t bar) { asm volatile("mbarrier.arrive.shared::cta.b64 _, [%0];" :: "r"(bar) : "memory"); }
__device__ __forceinline__ void mbar_arrive_cluster(uint32_t bar) { asm volatile("mbarrier.arrive.shared::cluster.b64 _, [%0];" :: "r"(bar) : "memory"); }
__device__ __forceinline__ bool mbar_try(uint32_t bar, uint32_t parity) {
    uint32_t ok;
    asm volatile("{\n.reg .pred p;\nmbarrier.try_wait.parity.shared::cta.b64 p, [%1], %2;\nselp.u32 %0, 1, 0, p;\n}\n" : "=r"(ok) : "r"(bar), "r"(parity) : "memory");
    return ok;
}
__device__ __forceinline__ bool mbar_test(uint32_t bar, uint32_t parity) {
    uint32_t ok;
    asm volatile("{\n.reg .pred p;\nmbarrier.test_wait.parity.shared::cta.b64 p, [%1], %2;\nselp.u32 %0, 1, 0, p;\n}\n" : "=r"(ok) : "r"(bar), "r"(parity) : "memory");
    return ok;
}
__device__ __forceinline__ void fail_if(bool c) { asm volatile("{\n.reg .pred p;\nsetp.ne.u32 p, %0, 0;\n@p st.volatile.global.u32 [%1], %0;\n}\n" :: "r"((uint32_t)c), "l"(0ull) : "memory"); }
__device__ __forceinline__ void mbar_wait(uint32_t bar, uint32_t parity) {
    int n = 0;
    while (!mbar_try(bar, parity)) fail_if(++n > (1 << 20));
}
__device__ __forceinline__ void st_async(uint32_t addr, uint32_t v, uint32_t bar) {
    asm volatile("st.async.weak.shared::cluster.mbarrier::complete_tx::bytes.u32 [%0], %1, [%2];" :: "r"(addr), "r"(v), "r"(bar) : "memory");
}
__device__ __forceinline__ uint32_t mapa(uint32_t a, uint32_t cta) { uint32_t d; asm("mapa.shared::cluster.u32 %0, %1, %2;" : "=r"(d) : "r"(a), "r"(cta)); return d; }
__device__ __forceinline__ uint32_t lds32(uint32_t a) { uint32_t v; asm volatile("ld.shared.b32 %0, [%1];" : "=r"(v) : "r"(a)); return v; }
__device__ __forceinline__ uint4 lds128(uint32_t a) { uint4 v; asm volatile("ld.shared.v4.b32 {%0,%1,%2,%3}, [%4];" : "=r"(v.x), "=r"(v.y), "=r"(v.z), "=r"(v.w) : "r"(a)); return v; }
__device__ __forceinline__ uint32_t lds32v(uint32_t a) { uint32_t v; asm volatile("ld.volatile.shared.b32 %0, [%1];" : "=r"(v) : "r"(a) : "memory"); return v; }
__device__ __forceinline__ void sts32(uint32_t a, uint32_t v) { asm volatile("st.shared.b32 [%0], %1;" :: "r"(a), "r"(v) : "memory"); }
__device__ __forceinline__ uint32_t ld32(const void* a) { uint32_t v; asm volatile("ld.relaxed.gpu.global.u32 %0, [%1];" : "=r"(v) : "l"(a) : "memory"); return v; }
__device__ __forceinline__ uint4 ld128(const void* a) {
    uint4 v;
    asm volatile("{\n.reg .b64 s, t;\n.reg .b128 v;\nld.relaxed.gpu.global.L1::no_allocate.b128 v, [%4];\nmov.b128 {s, t}, v;\nmov.b64 {%0, %1}, s;\nmov.b64 {%2, %3}, t;\n}\n"
                 : "=r"(v.x), "=r"(v.y), "=r"(v.z), "=r"(v.w) : "l"(a) : "memory");
    return v;
}
__device__ __forceinline__ void ld128_if(bool c, const void* a, uint32_t& x, uint32_t& y, uint32_t& z, uint32_t& w) {
    asm volatile("{\n.reg .pred p;\n.reg .b64 s, t;\n.reg .b128 v;\nsetp.ne.u32 p, %5, 0;\nmov.b64 s, {%0, %1};\nmov.b64 t, {%2, %3};\nmov.b128 v, {s, t};\n"
                 "@p ld.relaxed.gpu.global.L1::no_allocate.b128 v, [%4];\nmov.b128 {s, t}, v;\nmov.b64 {%0, %1}, s;\nmov.b64 {%2, %3}, t;\n}\n"
                 : "+r"(x), "+r"(y), "+r"(z), "+r"(w) : "l"(a), "r"((uint32_t)c) : "memory");
}
__device__ __forceinline__ void ld32_if(bool c, const void* a, uint32_t& x) {
    asm volatile("{\n.reg .pred p;\nsetp.ne.u32 p, %2, 0;\n@p ld.relaxed.gpu.global.u32 %0, [%1];\n}\n" : "+r"(x) : "l"(a), "r"((uint32_t)c) : "memory");
}
__device__ __forceinline__ void mma_k8(float* c, uint2 a, uint32_t b) {
    asm volatile("mma.sync.aligned.m16n8k8.row.col.f32.bf16.bf16.f32 {%0,%1,%2,%3}, {%4,%5}, {%6}, {%0,%1,%2,%3};"
                 : "+f"(c[0]), "+f"(c[1]), "+f"(c[2]), "+f"(c[3]) : "r"(a.x), "r"(a.y), "r"(b));
}
__device__ __forceinline__ void mma_k16(float* d, uint2 a, uint2 a2, uint32_t b0, uint32_t b1, float c0, float c1, float c2, float c3) {
    asm volatile("mma.sync.aligned.m16n8k16.row.col.f32.bf16.bf16.f32 {%0,%1,%2,%3}, {%4,%5,%6,%7}, {%8,%9}, {%10,%11,%12,%13};"
                 : "=f"(d[0]), "=f"(d[1]), "=f"(d[2]), "=f"(d[3]) : "r"(a.x), "r"(a.y), "r"(a2.x), "r"(a2.y), "r"(b0), "r"(b1), "f"(c0), "f"(c1), "f"(c2), "f"(c3));
}
__device__ __forceinline__ uint32_t pack_bias(float lo, float hi, uint32_t bias2) {
    uint32_t p, o;
    asm("cvt.rn.bf16x2.f32 %0, %1, %2;" : "=r"(p) : "f"(hi), "f"(lo));
    asm("add.rn.bf16x2 %0, %1, %2;" : "=r"(o) : "r"(p), "r"(bias2));
    return o;
}

struct Params {
    const uint16_t* w; const uint16_t* bias; const uint8_t* x; uint4* scr; uint4* over;
    int ntok;
    int ntiles;
    int alltiles;
    int ncl;
    int nctas;
    int pfd, pk;
    int ta, lead1, pw, k1, pfs, pfs2;
    int te, leade, slope1;
    uint32_t zero;
    int nha, nht, trig;
    int nh, jh, jd, rel;
    int a, amagic, nfull;
};
template <bool HELPER> __device__ __forceinline__ int place(const Params& p, int m) {
    if (HELPER) return (m < p.nha ? (m >> 1) * (p.a + 2) + ((m & 1) ? p.a + 1 : p.a >> 1) : p.alltiles - p.nht - p.nha + m);
    const int blk = (int)(((uint64_t)min(m, p.nfull) * (uint32_t)p.amagic) >> 32), r = m - blk * p.a;
    return (m + 2 * blk + (m < p.nfull && r >= (p.a >> 1)));
}

template <bool HELPER>
__global__ void __launch_bounds__(NTHREADS, 1)
spgemm_kernel(const __grid_constant__ CUtensorMap tmx, const __grid_constant__ CUtensorMap tmo, const Params p) {
    extern __shared__ unsigned char smem_raw[];
    const uint32_t sb = ((uint32_t)__cvta_generic_to_shared(smem_raw) + 1023u) & ~1023u;
    const int tid = threadIdx.x, warp = __shfl_sync(~0u, tid >> 5, 0), lane = tid & 31;
    const uint32_t tstart = now();
    const int rank = blockIdx.x % CL, cid = blockIdx.x / CL;
    const uint32_t bar_full = sb + OFF_FULL, bar_empty = sb + OFF_EMPTY, tk = sb + OFF_TK;
    uint4 wv[4];
    const int wrow = warp * 16 + (lane & 3) * 4;
    uint32_t b0, b1;
    auto prep_load = [&](int prb) {
        const uint32_t f0 = (prb >> 2) * 64;
        const uint16_t* const pa = p.w + ((uint32_t)(rank * 192 + wrow) * D + f0 + (lane >> 2) * 8);
#pragma unroll
        for (int j = 0; j < 4; j++) wv[j] = __ldg((const uint4*)(pa + j * D));
        b0 = __ldg(p.bias + (f0 + lane)); b1 = __ldg(p.bias + (f0 + 32 + lane));
    };
    if (!HELPER && warp < 12 && cid < 36) prep_load(cid);

    if (warp >= 12) {
        asm volatile("setmaxnreg.dec.sync.aligned.u32 32;");
        uint32_t epoch = 0;
        if (tid == NCONS + 32) asm volatile("ld.relaxed.gpu.global.u32 %0, [%1];" : "=r"(epoch) : "l"(&g_epoch) : "memory");
        if (tid == NCONS) {
#pragma unroll
            for (int s = 0; s < NSLOT; s++) { mbar_init(bar_full + 8 * s, 1); mbar_init(bar_empty + 8 * s, HELPER ? 6 : 6 * CL); }
            mbar_init(sb + OFF_MBAR, 1); mbar_init(sb + OFF_MBAR + 8, 1);
            mbar_init(sb + OFF_GO, HELPER ? 4 : 4 * CL); mbar_init(sb + OFF_GO + 8, HELPER ? 4 : 4 * CL); mbar_init(sb + OFF_GO + 16, HELPER ? 4 : 4 * CL); mbar_init(sb + OFF_EPOCH, 1);
            mbar_init(sb + OFF_FB, 1); mbar_init(sb + OFF_FB + 8, 1); mbar_init(sb + OFF_FB + 16, 1);
            asm volatile("fence.mbarrier_init.release.cluster;" ::: "memory");
            mbar_expect_tx(sb + OFF_MBAR, 36 * 4);
            if (!HELPER) asm volatile("griddepcontrol.launch_dependents;");
            asm volatile("prefetch.tensormap [%0];" :: "l"(&tmo) : "memory");
            asm volatile("prefetch.tensormap [%0];" :: "l"(&tmx) : "memory");
        }
        __syncwarp();
        if (HELPER) asm volatile("bar.sync 0;" ::: "memory");
        else asm volatile("barrier.cluster.arrive.relaxed.aligned;\nbarrier.cluster.wait.aligned;" ::: "memory");
        uint64_t pol;
        asm volatile("createpolicy.fractional.L2::evict_first.b64 %0, 1.0;" : "=l"(pol));
        if (warp == 12) {
            const int ntiles = HELPER ? p.alltiles - p.ntiles : p.ntiles;
            if (!HELPER && rank != 0) {
                auto phys = [&](int m) { return m < ntiles ? place<false>(p, m) : p.alltiles - p.nht; };
                auto prefetch = [&](int t) {
                    const int rows = min(NT, p.ntok - t * NT), r0 = rows * (rank - 1) / 2, r1 = rows * rank / 2;
                    if (lane == 0 && r1 > r0)
                        asm volatile("cp.async.bulk.prefetch.L2.global [%0], %1;" :: "l"(p.x + (size_t)t * TILE_BYTES + r0 * (D * 2)), "r"((r1 - r0) * (D * 2)) : "memory");
                };
                const int u0 = phys(p.ncl), n0 = phys(NSLOT * p.ncl) - u0;
                for (int k = cid; k < n0; k += p.ncl) { wait_until(tstart + p.pfd + k * p.pk / p.ncl); prefetch(u0 + k); }
                const int ua = phys(p.ta), n1 = phys(p.ta + p.lead1) - ua;
                for (int k = cid; k < n1; k += p.ncl) { wait_until(tstart + p.pw + (min(k, p.k1) * p.pfs + max(k - p.k1, 0) * p.pfs2) / p.ncl); prefetch(ua + k); }
            } else {
                const uint32_t rtk = HELPER ? tk : mapa(tk, lane < CL ? lane : 0), rfull = HELPER ? bar_full : mapa(bar_full, lane < CL ? lane : 0);
                int s = 0; uint32_t ph = 1, drawn = 0;
                for (int j = 0;; j++) {
                    const int t = HELPER || j < NSLOT ? cid + j * p.ncl : (int)__shfl_sync(~0u, drawn, 0) + NSLOT * p.ncl;
                    const bool valid = t < ntiles;
                    const int row = (place<HELPER>(p, t) * NB) ^ p.zero;
                    if (j > 0 && j < NSLOT) {
#pragma unroll
                        for (int g = 0; g < 3; g++) if (blk_off(g) < OFF_X + (j + 1) * TILE_BYTES && blk_off(g) + BLK > OFF_X + j * TILE_BYTES) mbar_wait(sb + OFF_GO + 8 * g, 0);
                    }
                    mbar_wait(bar_empty + 8 * s, ph);
                    if (HELPER && valid && t >= p.nha) {
                        for (int n = 0; ld32(&g_ticket) - 1 < (uint32_t)p.trig; n++) { __nanosleep(200); fail_if(n > (1 << 22)); }
                    }
                    if (valid && lane == 0) {
                        if (HELPER)
                            asm volatile("cp.async.bulk.tensor.4d.shared::cluster.global.mbarrier::complete_tx::bytes.L2::cache_hint [%0], [%1, {%3, %3, %3, %4}], [%2], %5;"
                                         :: "r"(sb + OFF_X + s * TILE_BYTES), "l"(&tmx), "r"(bar_full + 8 * s), "r"(0), "r"(row), "l"(pol) : "memory");
                        else
                            asm volatile("cp.async.bulk.tensor.4d.shared::cluster.global.mbarrier::complete_tx::bytes.multicast::cluster.L2::cache_hint [%0], [%1, {%3, %3, %3, %4}], [%2], %5, %6;"
                                         :: "r"(sb + OFF_X + s * TILE_BYTES), "l"(&tmx), "r"(bar_full + 8 * s), "r"(0), "r"(row), "h"((uint16_t)((1u << CL) - 1)), "l"(pol) : "memory");
                    }
                    if (HELPER) {
                        if (lane == 0) { sts32(tk + ((j & 7) << 2), valid ? (uint32_t)t : NO_TILE); mbar_expect_tx(bar_full + 8 * s, valid ? TILE_BYTES : 0); }
                    } else if (lane < CL) {
                        asm volatile("mbarrier.arrive.expect_tx.shared::cluster.b64 _, [%0], %1;" :: "r"(rfull + 8 * s), "r"(valid ? TILE_BYTES + 4 : 4) : "memory");
                        st_async(rtk + ((j & 7) << 2), valid ? (uint32_t)t : NO_TILE, rfull + 8 * s);
                    }
                    if (!valid) break;
                    if (!HELPER && lane == 0 && t > p.ta) {
                        auto fr = [&](int m) { const int f = m + p.leade + max(0, (p.slope1 * (p.te - m)) >> 16); return f < ntiles ? place<false>(p, f) : p.alltiles - p.nht; };
                        const int u1 = fr(t);
                        for (int u = fr(t - 1); u < u1; u++)
                            asm volatile("cp.async.bulk.prefetch.L2.global [%0], %1;" :: "l"(p.x + (size_t)u * TILE_BYTES), "r"(min(NT, p.ntok - u * NT) * (D * 2)) : "memory");
                    }
                    if (!HELPER && lane == 0 && j >= NSLOT - 1) drawn = atomicInc(&g_ticket, ntiles - p.ncl * (NSLOT - 1) - 1);
                    if (++s == NSLOT) { s = 0; ph ^= 1; }
                }
            }
        } else {
            const int g = warp - 13;
            const uint32_t rempty = HELPER ? bar_empty : mapa(bar_empty, 0);
            if (g == 0 && lane == 0) { sts32(sb + OFF_EPOCH + 8, epoch); mbar_arrive(sb + OFF_EPOCH); }
            mbar_wait(bar_full, 0);
            uint32_t t = lds32v(tk), ph = 0;
            int s = 0, nheld = 0, nout = 0, hnext = p.nh == 0 ? -1 : p.jh;
            const int nh = p.nh + (g == 0);
            uint32_t held[NH + 1];
            auto store = [&](int buf, uint32_t tile) {
                asm volatile("cp.async.bulk.tensor.2d.global.shared::cta.bulk_group.L2::cache_hint [%0, {%2, %3}], [%1], %4;"
                             :: "l"(&tmo), "r"(sb + OFF_STG + (buf * 3 + g) * STG_BYTES), "r"((g * 3 + rank) * 64), "r"((place<HELPER>(p, tile)) * NT), "l"(pol) : "memory");
            };
            auto release = [&]() {
#pragma unroll
                for (int k = 0; k <= NH; k++) if (k >= nout && k < nheld && lane == 0) store(1 + k, held[k]);
                nout = nheld;
            };
            for (int i = 0;; i++) {
                bar_sync(BAR_SFULL + g, 160);
                const int s1 = s + 1 == NSLOT ? 0 : s + 1;
                if (s1 == 0) ph ^= 1;
                if (lane == 0 && g < 2) { if (HELPER) mbar_arrive(bar_empty + 8 * s); else mbar_arrive_cluster(rempty + 8 * s); }
                const bool ready = __all_sync(~0u, mbar_test(bar_full + 8 * s1, ph));
                if (ready) bar_arrive(BAR_G + g, 288);
                if (lane == 0) {
                    asm volatile("fence.proxy.async.shared::cta;" ::: "memory");
                    if (i != hnext) store(0, t);
                    asm volatile("cp.async.bulk.commit_group;" ::: "memory");
                    if (g == 2 && i == 0 && atomicInc(&g_passed, p.nctas - 1) == (uint32_t)p.nctas - 1) atomicAdd(&g_epoch, 1);
                }
                __syncwarp();
                if (i == hnext) {
#pragma unroll
                    for (int k = 0; k <= NH; k++) if (k == nheld) held[k] = t;
                    hnext = ++nheld < nh ? hnext + p.jd : -1;
                }
                s = s1;
                if (!ready) { mbar_wait(bar_full + 8 * s, ph); bar_arrive(BAR_G + g, 288); }
                t = lds32v(tk + (((i + 1) & 7) << 2));
                if (t >= (uint32_t)p.rel && nout < nheld) { release(); if (lane == 0) asm volatile("cp.async.bulk.commit_group;" ::: "memory"); }
                if (lane == 0) asm volatile("cp.async.bulk.wait_group.read 0;" ::: "memory");
                __syncwarp();
                if (t == NO_TILE) break;
                bar_arrive(BAR_SEMPTY + g, 160);
            }
        }
        __syncwarp();
        if (!HELPER) asm volatile("barrier.cluster.arrive.relaxed.aligned;\nbarrier.cluster.wait.aligned;" ::: "memory");
    } else {
        asm volatile("setmaxnreg.inc.sync.aligned.u32 160;");
        const int wg = warp >> 2, r = lane >> 2, q = lane & 3;
        uint32_t epoch;
        if (HELPER) asm volatile("bar.sync 0;" ::: "memory");
        else {
            int prb = cid;
            asm volatile("barrier.cluster.arrive.relaxed.aligned;" ::: "memory");
            if (prb >= 36) asm volatile("barrier.cluster.wait.aligned;" ::: "memory");
#pragma unroll 1
            for (int round = 0; prb < 36; prb += p.ncl, round++) {
                const uint32_t wsm = sb + OFF_WST, msk = sb + OFF_MSK + (round & 1) * 144, mbar = sb + OFF_MBAR + (round & 1) * 8;
                if (round) {
                    bar_sync(3, 384);
                    if (tid == 0) mbar_expect_tx(mbar, 36 * 4);
                    prep_load(prb);
                }
                const uint32_t tk2 = min2(min2(tie_key(wv[0].x, wv[1].x, wv[2].x, wv[3].x), tie_key(wv[0].y, wv[1].y, wv[2].y, wv[3].y)),
                                          min2(tie_key(wv[0].z, wv[1].z, wv[2].z, wv[3].z), tie_key(wv[0].w, wv[1].w, wv[2].w, wv[3].w)));
                const uint32_t mk = __ballot_sync(~0u, (tk2 & 0xFFFFu) == 0 || tk2 < 0x10000u);
                if (round == 0) asm volatile("barrier.cluster.wait.aligned;" ::: "memory");
                if (lane < CL) st_async(mapa(msk + (rank * 12 + warp) * 4, lane), mk, mapa(mbar, lane));
#pragma unroll
                for (int j = 0; j < 4; j++) {
                    const int row = wrow + j;
                    const uint32_t ad = wsm + row * 128 + (((lane >> 2) ^ ((row & 1) | ((row >> 1) & 6))) << 4);
                    asm volatile("st.shared.v4.b32 [%0], {%1,%2,%3,%4};" :: "r"(ad), "r"(wv[j].x), "r"(wv[j].y), "r"(wv[j].z), "r"(wv[j].w) : "memory");
                }
                if (warp >= 6) bar_arrive(1, 384);
                else {
                    bar_sync(1, 384);
                    mbar_wait(sb + OFF_EPOCH, 0);
                    epoch = lds32v(sb + OFF_EPOCH + 8);
                    uint8_t* const scr = (uint8_t*)p.scr + (epoch & 1) * SCR_END;
                    mbar_wait(mbar, (round >> 1) & 1);
                    uint32_t m0 = 0, m1 = 0;
                    if (lane < KSTEPS) asm volatile("ld.volatile.shared.v2.b32 {%0,%1}, [%2];" : "=r"(m0), "=r"(m1) : "r"(msk + 8 * lane) : "memory");
                    uint32_t c0 = m0 - ((m0 >> 1) & 0x55555555u), c1 = m1 - ((m1 >> 1) & 0x55555555u);
                    c0 = (c0 & 0x33333333u) + ((c0 >> 2) & 0x33333333u) + (c1 & 0x33333333u) + ((c1 >> 2) & 0x33333333u);
                    c1 = __reduce_add_sync(~0u, (c0 >> 4) & 0x0F0F0F0Fu); c0 = __reduce_add_sync(~0u, c0 & 0x0F0F0F0Fu);
                    auto key = [&](int v) { return ((((v & 1) ? c1 : c0) >> (4 * (v & 6))) & 0xFFu) * 8 + v; };
                    const uint32_t ku = key(lane & 7);
                    const uint32_t l0 = __ballot_sync(~0u, key(lane >> 3) < ku), l1 = __ballot_sync(~0u, key(4 + (lane >> 3)) < ku);
                    const int rk = __popc((l0 >> (lane & 7)) & 0x01010101u) + __popc((l1 >> (lane & 7)) & 0x01010101u);
                    const int pp = prb & 3;
                    const int ulo = __ffs(__ballot_sync(~0u, rk == pp)) - 1, uhi = __ffs(__ballot_sync(~0u, rk == 7 - pp)) - 1;
                    uint32_t lo[4], hi[4];
                    load_unit(wsm, warp, ulo, lane, lo); load_unit(wsm, warp, uhi, lane, hi);
                    const uint32_t mm = (((m0 >> (4 * ulo)) | (m0 >> (4 * uhi))) & 15u) | ((((m1 >> (4 * ulo)) | (m1 >> (4 * uhi))) & 15u) << 4);
                    const uint2 bias2 = make_uint2(__shfl_sync(~0u, ulo < 4 ? b0 : b1, (ulo * 8 + r) & 31) * 0x10001u, __shfl_sync(~0u, uhi < 4 ? b0 : b1, (uhi * 8 + r) & 31) * 0x10001u);
                    emit_step(lo, hi, mm, prb, rank * 6 + warp, lane, ulo | (uhi << 4), bias2, scr, p.over, epoch + 1);
                }
            }
            if (cid >= 36 || warp >= 6) { mbar_wait(sb + OFF_EPOCH, 0); epoch = lds32v(sb + OFF_EPOCH + 8); }
            if (warp >= 6) for (int i = blockIdx.x * 192 + tid - 192; i < SCR_END / 16; i += gridDim.x * 192) p.scr[(~epoch & 1) * (SCR_END / 16) + i] = make_uint4(0, 0, 0, 0);
        }
        if (HELPER) { mbar_wait(sb + OFF_EPOCH, 0); epoch = lds32v(sb + OFF_EPOCH + 8); }
        if (wg == 2) bar_arrive(BAR_T, 256);
        const int mt = wg * 3 + rank, rb = mt * 4 + (warp & 3);
        const uint8_t* const scr = (const uint8_t*)p.scr + (epoch & 1) * SCR_END + mt * BLK;
        const int fo = (warp & 3) * 512 + lane * 16, io = BLK_I + (warp & 3) * 128 + r * 16, sl = (r >> 1) * 8 + q * 2 + (r & 1), so = BLK_S + (warp & 3) * 2560 + sl * 16;
        const int mo = BLK_M + ((warp & 3) * KSTEPS + (q >> 1)) * 64 + r * 8 + (q & 1) * 4;
        if (!HELPER && cid < 36) bar_sync(2, 384);
        const uint32_t blk = sb + blk_off(wg);
        if (warp == 0) {
            if (HELPER || cid >= 36 || p.ncl < 36) for (int n = 0; __any_sync(~0u, ld32(scr + 17 * 2048 + fo) == 0); n++) fail_if(n > (1 << 22));
            if (lane < 3) {
                mbar_expect_tx(sb + OFF_FB + 8 * lane, BLK);
                asm volatile("cp.async.bulk.shared::cluster.global.mbarrier::complete_tx::bytes [%0], [%1], %2, [%3];"
                             :: "r"(sb + blk_off(lane)), "l"(scr + lane * 3 * BLK), "r"(BLK), "r"(sb + OFF_FB + 8 * lane) : "memory");
            }
        }
        uint32_t a[KSTEPS][4], meta[9];
        uint2 rv[5]; uint32_t ro[5];
        uint32_t info, bias_lo, bias_hi;
        {
            const uint8_t* const fp = scr + fo; const uint8_t* const ip = scr + io; const uint8_t* const sp = scr + so; const uint8_t* const mp = scr + mo;
            mbar_wait(sb + OFF_FB + 8 * wg, 0);
            uint4 i0 = lds128(blk + io), sv[5];
#pragma unroll
            for (int j = 0; j < 5; j++) sv[j] = lds128(blk + so + j * 512);
#pragma unroll
            for (int j = 0; j < 9; j++) meta[j] = lds32(blk + mo + j * 128);
#pragma unroll
            for (int k = 0; k < KSTEPS; k++) { const uint4 v = lds128(blk + fo + k * 2048); a[k][0] = v.x; a[k][1] = v.y; a[k][2] = v.z; a[k][3] = v.w; }
            for (int n = 0;; n++) {
                uint32_t lo = __vimin3_u32(__vimin3_u32(i0.x, meta[8], sv[0].z), sv[1].z, __vimin3_u32(sv[2].z, sv[3].z, sv[4].z));
#pragma unroll
                for (int j = 0; j < 8; j += 2) lo = __vimin3_u32(lo, meta[j], meta[j + 1]);
#pragma unroll
                for (int k = 0; k < KSTEPS; k += 2) lo = __vimin3_u32(lo, a[k][0], a[k + 1][0]);
                if (__all_sync(~0u, lo != 0)) break;
                fail_if(n > (1 << 20));
                ld128_if(i0.x == 0, ip, i0.x, i0.y, i0.z, i0.w);
#pragma unroll
                for (int j = 0; j < 5; j++) ld128_if(sv[j].z == 0, sp + j * 512, sv[j].x, sv[j].y, sv[j].z, sv[j].w);
#pragma unroll
                for (int j = 0; j < 9; j++) ld32_if(meta[j] == 0, mp + j * 128, meta[j]);
#pragma unroll
                for (int k = 0; k < KSTEPS; k++) ld128_if(a[k][0] == 0, fp + k * 2048, a[k][0], a[k][1], a[k][2], a[k][3]);
            }
            info = i0.x; bias_lo = i0.y; bias_hi = i0.z;
#pragma unroll
            for (int j = 0; j < 5; j++) { rv[j] = make_uint2(sv[j].x, sv[j].y); ro[j] = sv[j].z; }
        }
#pragma unroll
        for (int j = 0; j < 4; j++) { rv[j].x ^= p.zero; rv[j].y ^= p.zero; }
        if ((wg || !BLK_FITS) && lane == 0) { if (HELPER) mbar_arrive(sb + OFF_GO + 8 * wg); else mbar_arrive_cluster(mapa(sb + OFF_GO + 8 * wg, 0)); }
        info = __shfl_sync(~0u, info, 0);
        const int ngrp = info & 0xFF, ulo = (info >> 8) & 7, uhi = (info >> 12) & 7;
#pragma unroll 1
        for (int j = 5; j < ngrp; j++)
            for (int n = 0; __any_sync(~0u, ld128(p.over + (rb * 36 + j) * 32 + sl).w != epoch + 1); n++) fail_if(n > (1 << 20));
        mbar_wait(bar_full, 0);
        const uint32_t stg = sb + OFF_STG + wg * STG_BYTES + ((lane >> 4) * 8 + (lane & 7)) * 128 + (((((lane >> 3) & 1) ? uhi : ulo) ^ (lane & 7)) << 4);
        float acc[NACC];
        uint32_t bq[NB][2], b4[NB];
        auto gather = [&](uint32_t xb) {
#pragma unroll
            for (int j = 0; j < 3; j++)
#pragma unroll
                for (int n = 0; n < NB; n++) { const uint32_t v = lds32(xb + ro[j] + (n * 9216 - RO_BIAS)); if (j < 2) acc[4 * n + j] = __uint_as_float(v); else bq[n][0] = v; }
            if (ngrp > 3) {
#pragma unroll
                for (int n = 0; n < NB; n++) bq[n][1] = lds32(xb + ro[3] + (n * 9216 - RO_BIAS));
                if (ngrp > 4) {
#pragma unroll
                    for (int n = 0; n < NB; n++) b4[n] = lds32(xb + ro[4] + (n * 9216 - RO_BIAS));
                }
            }
        };
        const int me = tid >> 7, nxt = __shfl_sync(~0u, BAR_T + (me == 2 ? 0 : me + 1), 0), prv = __shfl_sync(~0u, BAR_G + (me == 0 ? 2 : me - 1), 0);
#pragma unroll
        for (int n = 0; n < NB; n++) b4[n] = bq[n][1] = 0;
        gather(sb + OFF_X);
        bar_sync(BAR_T + wg, 256);
        auto bdesc = [](uint32_t x) { return ((uint64_t)1 << 62) | ((uint64_t)(9216 >> 4) << 32) | ((uint64_t)1 << 16) | (uint64_t)(x >> 4); };
        uint32_t xb = sb + OFF_X;
        uint64_t desc = bdesc(xb);
        const uint32_t re0 = HELPER ? bar_empty : mapa(bar_empty, 0);
        uint32_t re = re0;
        const bool releases = tid >= 256 && lane == 0;
        int hnext = p.nh == 0 ? -1 : p.jh, hbuf = 3 * STG_BYTES;
        bool more = true;
        for (int i = 0; more; i++) {
            auto rows03 = [&]() {
#pragma unroll
                for (int n = 0; n < NB; n++) mma_k16(acc + 4 * n, rv[0], rv[1], __float_as_uint(acc[4 * n]), __float_as_uint(acc[4 * n + 1]), 0.f, 0.f, 0.f, 0.f);
#pragma unroll
                for (int n = 0; n < NB; n++) mma_k16(acc + 4 * n, rv[2], rv[3], bq[n][0], bq[n][1], acc[4 * n], acc[4 * n + 1], acc[4 * n + 2], acc[4 * n + 3]);
            };
            if (ngrp <= 4) rows03();
            else {
                rows03();
#pragma unroll
                for (int n = 0; n < NB; n++) mma_k8(acc + 4 * n, rv[4], b4[n]);
#pragma unroll 1
                for (int j = 5; j < ngrp; j++) {
                    const uint4 o = __ldca(p.over + (rb * 36 + j) * 32 + sl);
#pragma unroll
                    for (int n = 0; n < NB; n++) b4[n] = lds32(xb + o.z + (n * 9216 - RO_BIAS));
#pragma unroll
                    for (int n = 0; n < NB; n++) mma_k8(acc + 4 * n, make_uint2(o.x, o.y), b4[n]);
                }
            }
            asm volatile("wgmma.fence.sync.aligned;" ::: "memory");
#pragma unroll
            for (int k = 0; k < KSTEPS; k++) {
                const uint64_t d = desc + (uint64_t)(((k >> 1) * 1024 + (k & 1) * 64) >> 4);
                if (k & 1) wgmma_sp<1>(acc, a[k], d, meta[k >> 1]);
                else       wgmma_sp<0>(acc, a[k], d, meta[k >> 1]);
                if (k == SPLIT - 1) asm volatile("wgmma.commit_group.sync.aligned;" ::: "memory");
            }
            asm volatile("wgmma.commit_group.sync.aligned;" ::: "memory");
            bar_arrive(nxt, 256);
            xb = xb == sb + OFF_X + (NSLOT - 1) * TILE_BYTES ? sb + OFF_X : xb + TILE_BYTES;
            desc = bdesc(xb);
            uint32_t sq = stg;
            if (i == hnext) { sq += hbuf; hbuf += 3 * STG_BYTES; hnext = hbuf <= (p.nh + (wg == 0)) * 3 * STG_BYTES ? hnext + p.jd : -1; }
            asm volatile("wgmma.wait_group.sync.aligned 1;" ::: "memory");
            if (wg != 0 || i != 0) bar_arrive(prv, 288);
            if (i != 0) bar_sync(BAR_SEMPTY + me, 160);
            asm volatile("wgmma.wait_group.sync.aligned 0;" ::: "memory");
            if (releases) { if (HELPER) mbar_arrive(re); else mbar_arrive_cluster(re); }
            re = re == re0 + 8 * (NSLOT - 1) ? re0 : re + 8;
#pragma unroll
            for (int n = 0; n + 1 < NB; n += 2) {
                const uint32_t p0 = pack_bias(acc[4 * n], acc[4 * n + 1], bias_lo), p1 = pack_bias(acc[4 * n + 2], acc[4 * n + 3], bias_hi);
                const uint32_t p2 = pack_bias(acc[4 * n + 4], acc[4 * n + 5], bias_lo), p3 = pack_bias(acc[4 * n + 6], acc[4 * n + 7], bias_hi);
                asm volatile("stmatrix.sync.aligned.m8n8.x4.trans.shared.b16 [%0], {%1,%2,%3,%4};" :: "r"(sq + n * 1024), "r"(p0), "r"(p1), "r"(p2), "r"(p3) : "memory");
            }
            if (NB & 1) {
                const uint32_t p0 = pack_bias(acc[NACC - 4], acc[NACC - 3], bias_lo), p1 = pack_bias(acc[NACC - 2], acc[NACC - 1], bias_hi);
                asm volatile("stmatrix.sync.aligned.m8n8.x2.trans.shared.b16 [%0], {%1,%2};" :: "r"(sq + (NB - 1) * 1024), "r"(p0), "r"(p1) : "memory");
            }
            bar_arrive(BAR_SFULL + me, 160);
            bar_sync(BAR_G + me, 288);
            const uint32_t tn = lds32v(tk + (((i + 1) & 7) << 2));
            gather(xb);
            more = __any_sync(~0u, tn != NO_TILE);
            if (more || wg == 0) bar_sync(BAR_T + me, 256);
        }
        if (wg == 0) bar_arrive(BAR_G + 2, 288);
        __syncwarp();
        if (!HELPER) asm volatile("barrier.cluster.arrive.relaxed.aligned;\nbarrier.cluster.wait.aligned;" ::: "memory");
    }
}

typedef CUresult (*EncodeFn)(CUtensorMap*, CUtensorMapDataType, cuuint32_t, void*, const cuuint64_t*, const cuuint64_t*, const cuuint32_t*, const cuuint32_t*,
                             CUtensorMapInterleave, CUtensorMapSwizzle, CUtensorMapL2promotion, CUtensorMapFloatOOBfill);

extern "C" void kernel_launch(void* const* d_in, const int* in_sizes, int n_in, void* d_out, int out_size) {
    static EncodeFn enc = nullptr;
    static int ncl = 0, nhelp = 0;
    const int ntok = in_sizes[0] / D;
    cudaLaunchConfig_t cfg = {};
    cudaLaunchAttribute at[1];
    at[0].id = cudaLaunchAttributeClusterDimension; at[0].val.clusterDim.x = CL; at[0].val.clusterDim.y = 1; at[0].val.clusterDim.z = 1;
    cfg.blockDim = dim3(NTHREADS); cfg.dynamicSmemBytes = SMEM_BYTES; cfg.attrs = at; cfg.numAttrs = 1; cfg.stream = cudaStreamPerThread;
    if (!enc) {
        cudaDriverEntryPointQueryResult qr; void* fn = nullptr;
        cudaGetDriverEntryPoint("cuTensorMapEncodeTiled", &fn, cudaEnableDefault, &qr);
        enc = (EncodeFn)fn;
        cudaFuncSetAttribute(spgemm_kernel<false>, cudaFuncAttributeMaxDynamicSharedMemorySize, SMEM_BYTES);
        cudaFuncSetAttribute(spgemm_kernel<true>, cudaFuncAttributeMaxDynamicSharedMemorySize, SMEM_BYTES);
        int dev = 0, nsm = 0;
        cudaGetDevice(&dev);
        cudaDeviceGetAttribute(&nsm, cudaDevAttrMultiProcessorCount, dev);
        cfg.gridDim = dim3(CL * (nsm / CL));
        cudaOccupancyMaxActiveClusters(&ncl, spgemm_kernel<false>, &cfg);
        if (ncl < 1) ncl = 1;
        nhelp = nsm > CL * ncl ? (nsm - CL * ncl) / CL : 0;
    }
    CUtensorMap tmx, tmo;
    {
        cuuint64_t dims[4] = {64, 8, 9, (cuuint64_t)(ntok / 8)};
        cuuint64_t strides[3] = {D * 2, 128, 8 * D * 2};
        cuuint32_t box[4] = {64, 8, 9, NB}, es[4] = {1, 1, 1, 1};
        enc(&tmx, CU_TENSOR_MAP_DATA_TYPE_BFLOAT16, 4, d_in[0], dims, strides, box, es, CU_TENSOR_MAP_INTERLEAVE_NONE,
            CU_TENSOR_MAP_SWIZZLE_128B, CU_TENSOR_MAP_L2_PROMOTION_L2_128B, CU_TENSOR_MAP_FLOAT_OOB_FILL_NONE);
    }
    {
        cuuint64_t dims[2] = {D, (cuuint64_t)ntok};
        cuuint64_t strides[1] = {D * 2};
        cuuint32_t box[2] = {64, NT}, es[2] = {1, 1};
        enc(&tmo, CU_TENSOR_MAP_DATA_TYPE_BFLOAT16, 2, d_out, dims, strides, box, es, CU_TENSOR_MAP_INTERLEAVE_NONE,
            CU_TENSOR_MAP_SWIZZLE_128B, CU_TENSOR_MAP_L2_PROMOTION_NONE, CU_TENSOR_MAP_FLOAT_OOB_FILL_NONE);
    }
    Params p;
    p.w = (const uint16_t*)d_in[1]; p.bias = (const uint16_t*)d_in[2]; p.x = (const uint8_t*)d_in[0];
    p.ntok = ntok;
    cudaGetSymbolAddress((void**)&p.scr, g_scr); cudaGetSymbolAddress((void**)&p.over, g_over);
    p.zero = 0;
    p.alltiles = (ntok + NT - 1) / NT;
    const int nc = ncl < p.alltiles ? ncl : p.alltiles;
    p.a = nhelp ? (int)(2 * nc / (nhelp * 1.07) + 0.5) : 2;
    if (p.a < 2) p.a = 2;
    const int nblk = (int)(p.alltiles / (p.a + 2) * 0.65);
    const int nh = nhelp && 2 * nblk >= nhelp && p.alltiles - 2 * nblk >= nc ? nhelp : 0;
    p.nha = nh ? 2 * nblk : 0; p.nht = p.alltiles > 16 * nc ? nh : 0;
    p.ntiles = p.alltiles - p.nha - p.nht;
    p.trig = p.ntiles - nc * NSLOT - 30;
    p.nfull = nh ? nblk * p.a : 0; p.amagic = (int)(0xFFFFFFFFu / (uint32_t)p.a + 1);
    p.ncl = nc; p.nctas = CL * (nc + nh);
    p.nh = (int)NH; p.jh = 4; p.jd = 4; p.rel = p.ntiles - 50;
    auto tiles = [](double v) { return (int)(v * 56 / NT); };
    auto ns = [](double v) { return (int)(v * NT / 56); };
    p.pfd = 1500; p.pk = ns(900);
    p.ta = (int)(p.ntiles * 0.4) + 1; p.lead1 = tiles(250); p.pw = 3000;
    p.k1 = tiles(68); p.pfs = ns(700); p.pfs2 = ns(2300);
    p.te = p.ntiles + 2; p.leade = tiles(50); p.slope1 = ((p.lead1 - p.leade) << 16) / (p.te - p.ta);
    cfg.gridDim = dim3(CL * nc);
    cudaLaunchKernelEx(&cfg, spgemm_kernel<false>, tmx, tmo, p);
    if (nh) {
        at[0].id = cudaLaunchAttributeProgrammaticStreamSerialization; at[0].val.programmaticStreamSerializationAllowed = 1;
        cfg.gridDim = dim3(CL * nh);
        p.ncl = nh;
        p.nh = p.nht ? NH : 0; p.jh = p.nha / nh - 10; p.jd = 1; p.rel = p.nha;
        cudaLaunchKernelEx(&cfg, spgemm_kernel<true>, tmx, tmo, p);
    }
}
```

```cpp
#include <cuda_runtime.h>
#include <cuda_bf16.h>
#include <cuda.h>
#include <stdint.h>

constexpr int D = 576;
constexpr int NH = 2;
constexpr int NT = 48;
constexpr int NSLOT = 3;
constexpr int SPLIT = 13;
constexpr int KSTEPS = 18;
constexpr int CL = 3;
constexpr int TILE_BYTES = NT * D * 2;
constexpr int STG_BYTES = NT * 128;
constexpr int NACC = NT / 2;
constexpr int NB = NT / 8;
constexpr int NCONS = 384;
constexpr int NTHREADS = 512;
constexpr uint32_t NO_TILE = 0xFFFFFFFFu;

constexpr int OFF_X = 0;
constexpr int OFF_STG = OFF_X + NSLOT * TILE_BYTES;
constexpr int OFF_WST = OFF_STG;
constexpr int OFF_FULL = OFF_STG + ((1 + NH) * 3 + 1) * STG_BYTES;
constexpr int OFF_EMPTY = OFF_FULL + 8 * NSLOT;
constexpr int OFF_MBAR = OFF_EMPTY + 8 * NSLOT;
constexpr int OFF_GO = OFF_MBAR + 16;
constexpr int OFF_FB = OFF_GO + 24;
constexpr int OFF_EPOCH = OFF_FB + 24;
constexpr int OFF_TK = OFF_EPOCH + 16;
constexpr int OFF_MSK = OFF_TK + 32;
constexpr int SMEM_BYTES = OFF_MSK + 2 * 36 * 4 + 1024;
static_assert(SMEM_BYTES <= 232448 && NSLOT < 8 && NSLOT >= 3, "layout");
constexpr int BAR_T = 4, BAR_SFULL = 7, BAR_SEMPTY = 10, BAR_G = 13;

constexpr int BLK_M = KSTEPS * 2048, BLK_S = BLK_M + 4 * KSTEPS * 64, BLK_I = BLK_S + 4 * 2560, BLK = BLK_I + 4 * 128, SCR_END = 9 * BLK;
constexpr bool BLK_FITS = BLK <= TILE_BYTES && BLK <= OFF_FULL - OFF_STG;
__host__ __device__ constexpr int blk_off(int g) { return BLK_FITS ? (g == 0 ? OFF_STG : OFF_X + g * TILE_BYTES) : OFF_X + TILE_BYTES + (g + 2) % 3 * BLK; }
static_assert(blk_off(0) + BLK <= OFF_FULL && blk_off(2) + BLK <= OFF_STG && OFF_WST + 192 * 128 <= OFF_FULL, "fragment blocks");
__device__ __align__(128) uint4    g_scr[2][SCR_END / 16];
__device__ __align__(128) uint4    g_over[36 * 144 * 8];
__device__ __align__(128) uint32_t g_epoch;
__device__ __align__(128) uint32_t g_passed;
__device__ __align__(128) uint32_t g_ticket;

__device__ __forceinline__ uint32_t now() { uint32_t c; asm volatile("mov.u32 %0, %%globaltimer_lo;" : "=r"(c)); return c; }
__device__ __forceinline__ void wait_until(uint32_t due) { while ((int)(now() - due) < 0) __nanosleep(20); }

__device__ __forceinline__ uint32_t max2(uint32_t a, uint32_t b) { uint32_t d; asm("max.u16x2 %0, %1, %2;" : "=r"(d) : "r"(a), "r"(b)); return d; }
__device__ __forceinline__ uint32_t min2(uint32_t a, uint32_t b) { uint32_t d; asm("min.u16x2 %0, %1, %2;" : "=r"(d) : "r"(a), "r"(b)); return d; }
__device__ __forceinline__ uint32_t sign2(uint32_t a) { uint32_t d; asm("prmt.b32 %0, %1, %1, 0xBB99;" : "=r"(d) : "r"(a)); return d; }
__device__ __forceinline__ void zip4(uint32_t a01, uint32_t a23, uint32_t b01, uint32_t b23, uint32_t (&x)[4]) {
    x[0] = __byte_perm(a01, b01, 0x5410); x[1] = __byte_perm(a01, b01, 0x7632); x[2] = __byte_perm(a23, b23, 0x5410); x[3] = __byte_perm(a23, b23, 0x7632);
}
__device__ __forceinline__ void middle2(const uint32_t (&x)[4], uint32_t (&m)[4], uint32_t& u, uint32_t& v) {
#pragma unroll
    for (int i = 0; i < 4; i++) m[i] = x[i] & 0x7FFF7FFFu;
    u = min2(max2(m[0], m[1]), max2(m[2], m[3])); v = max2(min2(m[0], m[1]), min2(m[2], m[3]));
}
__device__ __forceinline__ uint32_t tie_key(uint32_t x0, uint32_t x1, uint32_t x2, uint32_t x3) {
    const uint32_t x[4] = {x0, x1, x2, x3};
    uint32_t m[4], u, v;
    middle2(x, m, u, v);
    return max2(u, 0x00010001u) ^ v;
}
__device__ __forceinline__ void load_unit(uint32_t wsm, int ls, int unit, int lane, uint32_t (&m)[4]) {
    const int row = ls * 32 + (lane >> 4) * 16 + ((lane & 7) >> 1) * 4 + ((lane >> 3) & 1) * 2 + (lane & 1);
    const uint32_t ad = wsm + row * 128 + ((unit ^ ((row & 1) | ((row >> 1) & 6))) << 4);
    asm volatile("ldmatrix.sync.aligned.m8n8.x4.trans.shared.b16 {%0,%1,%2,%3}, [%4];" : "=r"(m[0]), "=r"(m[1]), "=r"(m[2]), "=r"(m[3]) : "r"(ad) : "memory");
}
__device__ __forceinline__ void split_pair(const uint32_t (&x)[4], bool P, uint32_t& alo, uint32_t& ahi, uint32_t& nib, uint32_t& rlo, uint32_t& rhi) {
    uint32_t m[4], u, v;
    middle2(x, m, u, v);
    const uint32_t c = 0x80008000u - max2(max2(u, v), 0x00010001u);
    uint32_t k0 = sign2(m[0] + c), k1 = sign2(m[1] + c), k2 = sign2(m[2] + c), k3 = sign2(m[3] + c);
    const uint32_t three = (k0 & k1 & (k2 | k3)) | (k2 & k3 & (k0 | k1)), four = k0 & k1 & k2 & k3;
    const uint32_t pa = P ? k2 : k0, pb = P ? k3 : k1;
    const uint32_t ra = three & pa, rb = three & pb & (four | ~pa);
    const uint32_t va = (P ? x[2] : x[0]) & ra, vb = (P ? x[3] : x[1]) & rb;
    if (P) { k2 &= ~ra; k3 &= ~rb; } else { k0 &= ~ra; k1 &= ~rb; }
    const uint32_t s1 = k1 & k0, s2 = k2 & (k0 | k1);
    const uint32_t t = (k1 & x[1]) | (~k1 & k2 & x[2]);
    const uint32_t x0 = (k0 & x[0]) | (~k0 & t), x1 = (s1 & x[1]) | (s2 & x[2]) | (k3 & x[3]);
    nib = (~k0 & k1 & 0x00010001u) | (~k0 & ~k1 & 0x00020002u) | (~s2 & 0x00040004u) | (~s1 & 0x00080008u);
    alo = __byte_perm(x0, x1, 0x5410); ahi = __byte_perm(x0, x1, 0x7632);
    rlo = __byte_perm(va, vb, 0x5410); rhi = __byte_perm(va, vb, 0x7632);
}
__device__ __forceinline__ uint32_t nonzero(uint32_t v) { return v ? v : 0x8000u; }
__device__ __forceinline__ void pub32(void* a, uint32_t v) { asm volatile("st.relaxed.gpu.global.u32 [%0], %1;" :: "l"(a), "r"(v) : "memory"); }
__device__ __forceinline__ void pub128(bool c, void* a, uint32_t x, uint32_t y, uint32_t z, uint32_t w) {
    asm volatile("{\n.reg .pred p;\n.reg .b64 s, t;\n.reg .b128 v;\nsetp.ne.u32 p, %5, 0;\nmov.b64 s, {%1, %2};\nmov.b64 t, {%3, %4};\nmov.b128 v, {s, t};\n@p st.relaxed.gpu.global.b128 [%0], v;\n}\n"
                 :: "l"(a), "r"(x), "r"(y), "r"(z), "r"(w), "r"((uint32_t)c) : "memory");
}
constexpr int RO_BIAS = 16;
__device__ __forceinline__ uint32_t resid_off(int g, int P, int r) {
    int k0 = 4 * g + 2 * P;
    int chunk = k0 >> 6, byte = (k0 & 63) * 2;
    return chunk * 1024 + r * 128 + (((byte >> 4) ^ r) << 4) + (byte & 15);
}
__device__ __forceinline__ void emit_step(const uint32_t (&lo)[4], const uint32_t (&hi)[4], uint32_t mm, int rb, int ks, int lane, uint32_t units, uint2 bias2,
                                          uint8_t* scr, uint4* over, uint32_t tag) {
    scr += (rb >> 2) * BLK;
    const int wp = rb & 3;
    const int lo16 = (lane >> 3) * 128 + ((lane >> 2) & 1) * 16;
    uint8_t* const s0 = scr + BLK_S + wp * 2560 + lo16;
    uint8_t* const s1 = (uint8_t*)(over + rb * 144 * 8) + lo16;
    auto put_slot = [&](bool c, int sl, uint32_t v0, uint32_t v1, uint32_t off) {
        pub128(c, (sl < 20 ? s0 : s1) + (sl >> 2) * 512 + (sl & 3) * 32, v0, v1, off + RO_BIAS, tag);
    };
    const int r = lane >> 2, q = lane & 3, g0 = ks * 8 + q, g1 = g0 + 4;
    const uint32_t gm = __shfl_sync(~0u, mm, ks);
    const uint32_t c2 = __popc(mm & 0x55u) | (__popc(mm & 0xAAu) << 16);
    const uint32_t tot = __reduce_add_sync(~0u, c2), pre = __reduce_add_sync(~0u, lane < ks ? c2 : 0u);
    const int ne = tot & 0xFFFF, no = tot >> 16;
    const uint32_t par = (q & 1) ? 0xAAu : 0x55u;
    const int base = (q & 1) ? pre >> 16 : pre & 0xFFFF;
    const int rk0 = base + __popc(gm & par & ((1u << q) - 1)), rk1 = base + __popc(gm & par & ((16u << q) - 1));
    uint32_t a[4], rs[4], x[4], w0, w1;
    zip4(lo[0], lo[1], hi[0], hi[1], x); split_pair(x, rk0 & 1, a[0], a[1], w0, rs[0], rs[1]);
    zip4(lo[2], lo[3], hi[2], hi[3], x); split_pair(x, rk1 & 1, a[2], a[3], w1, rs[2], rs[3]);
    pub128(true, scr + ks * 2048 + wp * 512 + lane * 16, nonzero(a[0]), a[1], a[2], a[3]);
    w0 <<= 4 * q; w1 <<= 4 * q;
    w0 |= __shfl_xor_sync(~0u, w0, 1); w1 |= __shfl_xor_sync(~0u, w1, 1);
    w0 |= __shfl_xor_sync(~0u, w0, 2); w1 |= __shfl_xor_sync(~0u, w1, 2);
    if (q < 2) pub32(scr + BLK_M + (wp * KSTEPS + ks) * 64 + r * 8 + q * 4, q ? w1 : w0);
    const int em = min(ne, max(8, 16 - no)), om = min(no, 16 - em);
    const int odd = q & 1, m = odd ? om : em;
#pragma unroll
    for (int e = 0; e < 2; e++) {
        const int rk = e ? rk1 : rk0, t = 15 - rk;
        const int u = min(rk, t), in = (u >> 1) * 4 + (u & 1) + 2 * (odd ^ (rk >> 3 & 1)), out = 16 + (odd ? ne - em : 0) + rk - m;
        const int sl = rk >= m ? out : in;
        put_slot((gm >> (4 * e + q)) & 1, sl, rs[2 * e], rs[2 * e + 1], resid_off(e ? g1 : g0, rk & 1, r));
    }
    const int ntot = ne + no;
    const int ng = ntot > 16 ? (ntot + 3) >> 2 : min(4, (max(ne, no) + 1) >> 1);
    pub128(ks == 7 && q == 0, scr + BLK_I + wp * 128 + r * 16, ng | (units << 8), bias2.x, bias2.y, 0);
    const int idx = 2 * ks + (q & 1);
    const int frow = ks < 5 ? ks : ng - 1;
    const bool fill = ks < 4 ? !(idx < ((q >> 1) ? om : em) || (15 - idx) < ((q >> 1) ? em : om)) : (ks == 4 || (ks == 5 && ng > 5)) && 4 * frow + q >= ntot;
    put_slot(fill, frow * 4 + q, 0, 0, resid_off(q >> 1, q & 1, r));
}

template<int SEL> __device__ __forceinline__ void wgmma_sp(float (&d)[NACC], const uint32_t (&a)[4], uint64_t bdesc, uint32_t meta) {
    asm volatile("wgmma.mma_async.sp.sync.aligned.m64n48k32.f32.bf16.bf16 {%0, %1, %2, %3, %4, %5, %6, %7, %8, %9, %10, %11, %12, %13, %14, %15, %16, %17, %18, %19, %20, %21, %22, %23}, {%24, %25, %26, %27}, %28, %29, %30, 1, 1, 1, 0;"
        : "+f"(d[0]), "+f"(d[1]), "+f"(d[2]), "+f"(d[3]), "+f"(d[4]), "+f"(d[5]), "+f"(d[6]), "+f"(d[7]), "+f"(d[8]), "+f"(d[9]), "+f"(d[10]), "+f"(d[11]), "+f"(d[12]), "+f"(d[13]), "+f"(d[14]), "+f"(d[15]), "+f"(d[16]), "+f"(d[17]), "+f"(d[18]), "+f"(d[19]), "+f"(d[20]), "+f"(d[21]), "+f"(d[22]), "+f"(d[23])
        : "r"(a[0]), "r"(a[1]), "r"(a[2]), "r"(a[3]), "l"(bdesc), "r"(meta), "n"(SEL));
}
__device__ __forceinline__ void bar_sync(int id, int n) { asm volatile("bar.sync %0, %1;" :: "r"(id), "r"(n) : "memory"); }
__device__ __forceinline__ void bar_arrive(int id, int n) { asm volatile("bar.arrive %0, %1;" :: "r"(id), "r"(n) : "memory"); }

__device__ __forceinline__ void mbar_init(uint32_t bar, uint32_t cnt) { asm volatile("mbarrier.init.shared::cta.b64 [%0], %1;" :: "r"(bar), "r"(cnt) : "memory"); }
__device__ __forceinline__ void mbar_expect_tx(uint32_t bar, uint32_t bytes) {
    asm volatile("mbarrier.arrive.expect_tx.shared::cta.b64 _, [%0], %1;" :: "r"(bar), "r"(bytes) : "memory");
}
__device__ __forceinline__ void mbar_arrive(uint32_t bar) { asm volatile("mbarrier.arrive.shared::cta.b64 _, [%0];" :: "r"(bar) : "memory"); }
__device__ __forceinline__ void mbar_arrive_cluster(uint32_t bar) { asm volatile("mbarrier.arrive.shared::cluster.b64 _, [%0];" :: "r"(bar) : "memory"); }
__device__ __forceinline__ bool mbar_try(uint32_t bar, uint32_t parity) {
    uint32_t ok;
    asm volatile("{\n.reg .pred p;\nmbarrier.try_wait.parity.shared::cta.b64 p, [%1], %2;\nselp.u32 %0, 1, 0, p;\n}\n" : "=r"(ok) : "r"(bar), "r"(parity) : "memory");
    return ok;
}
__device__ __forceinline__ bool mbar_test(uint32_t bar, uint32_t parity) {
    uint32_t ok;
    asm volatile("{\n.reg .pred p;\nmbarrier.test_wait.parity.shared::cta.b64 p, [%1], %2;\nselp.u32 %0, 1, 0, p;\n}\n" : "=r"(ok) : "r"(bar), "r"(parity) : "memory");
    return ok;
}
__device__ __forceinline__ void fail_if(bool c) { asm volatile("{\n.reg .pred p;\nsetp.ne.u32 p, %0, 0;\n@p st.volatile.global.u32 [%1], %0;\n}\n" :: "r"((uint32_t)c), "l"(0ull) : "memory"); }
__device__ __forceinline__ void mbar_wait(uint32_t bar, uint32_t parity) {
    int n = 0;
    while (!mbar_try(bar, parity)) fail_if(++n > (1 << 20));
}
__device__ __forceinline__ void st_async(uint32_t addr, uint32_t v, uint32_t bar) {
    asm volatile("st.async.weak.shared::cluster.mbarrier::complete_tx::bytes.u32 [%0], %1, [%2];" :: "r"(addr), "r"(v), "r"(bar) : "memory");
}
__device__ __forceinline__ uint32_t mapa(uint32_t a, uint32_t cta) { uint32_t d; asm("mapa.shared::cluster.u32 %0, %1, %2;" : "=r"(d) : "r"(a), "r"(cta)); return d; }
__device__ __forceinline__ uint32_t lds32(uint32_t a) { uint32_t v; asm volatile("ld.shared.b32 %0, [%1];" : "=r"(v) : "r"(a)); return v; }
__device__ __forceinline__ uint4 lds128(uint32_t a) { uint4 v; asm volatile("ld.shared.v4.b32 {%0,%1,%2,%3}, [%4];" : "=r"(v.x), "=r"(v.y), "=r"(v.z), "=r"(v.w) : "r"(a)); return v; }
__device__ __forceinline__ uint32_t lds32v(uint32_t a) { uint32_t v; asm volatile("ld.volatile.shared.b32 %0, [%1];" : "=r"(v) : "r"(a) : "memory"); return v; }
__device__ __forceinline__ void sts32(uint32_t a, uint32_t v) { asm volatile("st.shared.b32 [%0], %1;" :: "r"(a), "r"(v) : "memory"); }
__device__ __forceinline__ uint32_t ld32(const void* a) { uint32_t v; asm volatile("ld.relaxed.gpu.global.u32 %0, [%1];" : "=r"(v) : "l"(a) : "memory"); return v; }
__device__ __forceinline__ uint4 ld128(const void* a) {
    uint4 v;
    asm volatile("{\n.reg .b64 s, t;\n.reg .b128 v;\nld.relaxed.gpu.global.L1::no_allocate.b128 v, [%4];\nmov.b128 {s, t}, v;\nmov.b64 {%0, %1}, s;\nmov.b64 {%2, %3}, t;\n}\n"
                 : "=r"(v.x), "=r"(v.y), "=r"(v.z), "=r"(v.w) : "l"(a) : "memory");
    return v;
}
__device__ __forceinline__ void ld128_if(bool c, const void* a, uint32_t& x, uint32_t& y, uint32_t& z, uint32_t& w) {
    asm volatile("{\n.reg .pred p;\n.reg .b64 s, t;\n.reg .b128 v;\nsetp.ne.u32 p, %5, 0;\nmov.b64 s, {%0, %1};\nmov.b64 t, {%2, %3};\nmov.b128 v, {s, t};\n"
                 "@p ld.relaxed.gpu.global.L1::no_allocate.b128 v, [%4];\nmov.b128 {s, t}, v;\nmov.b64 {%0, %1}, s;\nmov.b64 {%2, %3}, t;\n}\n"
                 : "+r"(x), "+r"(y), "+r"(z), "+r"(w) : "l"(a), "r"((uint32_t)c) : "memory");
}
__device__ __forceinline__ void ld32_if(bool c, const void* a, uint32_t& x) {
    asm volatile("{\n.reg .pred p;\nsetp.ne.u32 p, %2, 0;\n@p ld.relaxed.gpu.global.u32 %0, [%1];\n}\n" : "+r"(x) : "l"(a), "r"((uint32_t)c) : "memory");
}
__device__ __forceinline__ void mma_k8(float* c, uint2 a, uint32_t b) {
    asm volatile("mma.sync.aligned.m16n8k8.row.col.f32.bf16.bf16.f32 {%0,%1,%2,%3}, {%4,%5}, {%6}, {%0,%1,%2,%3};"
                 : "+f"(c[0]), "+f"(c[1]), "+f"(c[2]), "+f"(c[3]) : "r"(a.x), "r"(a.y), "r"(b));
}
__device__ __forceinline__ void mma_k16(float* d, uint2 a, uint2 a2, uint32_t b0, uint32_t b1, float c0, float c1, float c2, float c3) {
    asm volatile("mma.sync.aligned.m16n8k16.row.col.f32.bf16.bf16.f32 {%0,%1,%2,%3}, {%4,%5,%6,%7}, {%8,%9}, {%10,%11,%12,%13};"
                 : "=f"(d[0]), "=f"(d[1]), "=f"(d[2]), "=f"(d[3]) : "r"(a.x), "r"(a.y), "r"(a2.x), "r"(a2.y), "r"(b0), "r"(b1), "f"(c0), "f"(c1), "f"(c2), "f"(c3));
}
__device__ __forceinline__ uint32_t pack_bias(float lo, float hi, uint32_t bias2) {
    uint32_t p, o;
    asm("cvt.rn.bf16x2.f32 %0, %1, %2;" : "=r"(p) : "f"(hi), "f"(lo));
    asm("add.rn.bf16x2 %0, %1, %2;" : "=r"(o) : "r"(p), "r"(bias2));
    return o;
}

struct Params {
    const uint16_t* w; const uint16_t* bias; const uint8_t* x; uint4* scr; uint4* over;
    int ntok;
    int ntiles;
    int alltiles;
    int ncl;
    int nctas;
    int pfd, pk;
    int ta, lead1, pw, k1, pfs, pfs2;
    int te, leade, slope1;
    uint32_t zero;
    int nha, nht, trig;
    int nh, jh, jd, rel;
    int a, amagic, nfull;
};
template <bool HELPER> __device__ __forceinline__ int place(const Params& p, int m) {
    if (HELPER) return (m < p.nha ? (m >> 1) * (p.a + 2) + ((m & 1) ? p.a + 1 : p.a >> 1) : p.alltiles - p.nht - p.nha + m);
    const int blk = (int)(((uint64_t)min(m, p.nfull) * (uint32_t)p.amagic) >> 32), r = m - blk * p.a;
    return (m + 2 * blk + (m < p.nfull && r >= (p.a >> 1)));
}

template <bool HELPER>
__global__ void __launch_bounds__(NTHREADS, 1)
spgemm_kernel(const __grid_constant__ CUtensorMap tmx, const __grid_constant__ CUtensorMap tmo, const Params p) {
    extern __shared__ unsigned char smem_raw[];
    const uint32_t sb = ((uint32_t)__cvta_generic_to_shared(smem_raw) + 1023u) & ~1023u;
    const int tid = threadIdx.x, warp = __shfl_sync(~0u, tid >> 5, 0), lane = tid & 31;
    const uint32_t tstart = now();
    const int rank = blockIdx.x % CL, cid = blockIdx.x / CL;
    const uint32_t bar_full = sb + OFF_FULL, bar_empty = sb + OFF_EMPTY, tk = sb + OFF_TK;
    uint4 wv[4];
    const int wrow = warp * 16 + (lane & 3) * 4;
    uint32_t b0, b1;
    auto prep_load = [&](int prb) {
        const uint32_t f0 = (prb >> 2) * 64;
        const uint16_t* const pa = p.w + ((uint32_t)(rank * 192 + wrow) * D + f0 + (lane >> 2) * 8);
#pragma unroll
        for (int j = 0; j < 4; j++) wv[j] = __ldg((const uint4*)(pa + j * D));
        b0 = __ldg(p.bias + (f0 + lane)); b1 = __ldg(p.bias + (f0 + 32 + lane));
    };
    if (!HELPER && warp < 12 && cid < 36) prep_load(cid);

    if (warp >= 12) {
        asm volatile("setmaxnreg.dec.sync.aligned.u32 32;");
        uint32_t epoch = 0;
        if (tid == NCONS + 32) asm volatile("ld.relaxed.gpu.global.u32 %0, [%1];" : "=r"(epoch) : "l"(&g_epoch) : "memory");
        if (tid == NCONS) {
#pragma unroll
            for (int s = 0; s < NSLOT; s++) { mbar_init(bar_full + 8 * s, 1); mbar_init(bar_empty + 8 * s, HELPER ? 6 : 6 * CL); }
            mbar_init(sb + OFF_MBAR, 1); mbar_init(sb + OFF_MBAR + 8, 1);
            mbar_init(sb + OFF_GO, HELPER ? 4 : 4 * CL); mbar_init(sb + OFF_GO + 8, HELPER ? 4 : 4 * CL); mbar_init(sb + OFF_GO + 16, HELPER ? 4 : 4 * CL); mbar_init(sb + OFF_EPOCH, 1);
            mbar_init(sb + OFF_FB, 1); mbar_init(sb + OFF_FB + 8, 1); mbar_init(sb + OFF_FB + 16, 1);
            asm volatile("fence.mbarrier_init.release.cluster;" ::: "memory");
            mbar_expect_tx(sb + OFF_MBAR, 36 * 4);
            if (!HELPER) asm volatile("griddepcontrol.launch_dependents;");
            asm volatile("prefetch.tensormap [%0];" :: "l"(&tmo) : "memory");
            asm volatile("prefetch.tensormap [%0];" :: "l"(&tmx) : "memory");
        }
        __syncwarp();
        if (HELPER) asm volatile("bar.sync 0;" ::: "memory");
        else asm volatile("barrier.cluster.arrive.relaxed.aligned;\nbarrier.cluster.wait.aligned;" ::: "memory");
        uint64_t pol;
        asm volatile("createpolicy.fractional.L2::evict_first.b64 %0, 1.0;" : "=l"(pol));
        if (warp == 12) {
            const int ntiles = HELPER ? p.alltiles - p.ntiles : p.ntiles;
            if (!HELPER && rank != 0) {
                auto phys = [&](int m) { return m < ntiles ? place<false>(p, m) : p.alltiles - p.nht; };
                auto prefetch = [&](int t) {
                    const int rows = min(NT, p.ntok - t * NT), r0 = rows * (rank - 1) / 2, r1 = rows * rank / 2;
                    if (lane == 0 && r1 > r0)
                        asm volatile("cp.async.bulk.prefetch.L2.global [%0], %1;" :: "l"(p.x + (size_t)t * TILE_BYTES + r0 * (D * 2)), "r"((r1 - r0) * (D * 2)) : "memory");
                };
                const int u0 = phys(p.ncl), n0 = phys(NSLOT * p.ncl) - u0;
                for (int k = cid; k < n0; k += p.ncl) { wait_until(tstart + p.pfd + k * p.pk / p.ncl); prefetch(u0 + k); }
                const int ua = phys(p.ta), n1 = phys(p.ta + p.lead1) - ua;
                for (int k = cid; k < n1; k += p.ncl) { wait_until(tstart + p.pw + (min(k, p.k1) * p.pfs + max(k - p.k1, 0) * p.pfs2) / p.ncl); prefetch(ua + k); }
            } else {
                const uint32_t rtk = HELPER ? tk : mapa(tk, lane < CL ? lane : 0), rfull = HELPER ? bar_full : mapa(bar_full, lane < CL ? lane : 0);
                int s = 0; uint32_t ph = 1, drawn = 0;
                for (int j = 0;; j++) {
                    const int t = HELPER || j < NSLOT ? cid + j * p.ncl : (int)__shfl_sync(~0u, drawn, 0) + NSLOT * p.ncl;
                    const bool valid = t < ntiles;
                    const int row = (place<HELPER>(p, t) * NB) ^ p.zero;
                    if (j > 0 && j < NSLOT) {
#pragma unroll
                        for (int g = 0; g < 3; g++) if (blk_off(g) < OFF_X + (j + 1) * TILE_BYTES && blk_off(g) + BLK > OFF_X + j * TILE_BYTES) mbar_wait(sb + OFF_GO + 8 * g, 0);
                    }
                    mbar_wait(bar_empty + 8 * s, ph);
                    if (HELPER && valid && t >= p.nha) {
                        for (int n = 0; ld32(&g_ticket) - 1 < (uint32_t)p.trig; n++) { __nanosleep(200); fail_if(n > (1 << 22)); }
                    }
                    if (valid && lane == 0) {
                        if (HELPER)
                            asm volatile("cp.async.bulk.tensor.4d.shared::cluster.global.mbarrier::complete_tx::bytes.L2::cache_hint [%0], [%1, {%3, %3, %3, %4}], [%2], %5;"
                                         :: "r"(sb + OFF_X + s * TILE_BYTES), "l"(&tmx), "r"(bar_full + 8 * s), "r"(0), "r"(row), "l"(pol) : "memory");
                        else
                            asm volatile("cp.async.bulk.tensor.4d.shared::cluster.global.mbarrier::complete_tx::bytes.multicast::cluster.L2::cache_hint [%0], [%1, {%3, %3, %3, %4}], [%2], %5, %6;"
                                         :: "r"(sb + OFF_X + s * TILE_BYTES), "l"(&tmx), "r"(bar_full + 8 * s), "r"(0), "r"(row), "h"((uint16_t)((1u << CL) - 1)), "l"(pol) : "memory");
                    }
                    if (HELPER) {
                        if (lane == 0) { sts32(tk + ((j & 7) << 2), valid ? (uint32_t)t : NO_TILE); mbar_expect_tx(bar_full + 8 * s, valid ? TILE_BYTES : 0); }
                    } else if (lane < CL) {
                        asm volatile("mbarrier.arrive.expect_tx.shared::cluster.b64 _, [%0], %1;" :: "r"(rfull + 8 * s), "r"(valid ? TILE_BYTES + 4 : 4) : "memory");
                        st_async(rtk + ((j & 7) << 2), valid ? (uint32_t)t : NO_TILE, rfull + 8 * s);
                    }
                    if (!valid) break;
                    if (!HELPER && lane == 0 && t > p.ta) {
                        auto fr = [&](int m) { const int f = m + p.leade + max(0, (p.slope1 * (p.te - m)) >> 16); return f < ntiles ? place<false>(p, f) : p.alltiles - p.nht; };
                        const int u1 = fr(t);
                        for (int u = fr(t - 1); u < u1; u++)
                            asm volatile("cp.async.bulk.prefetch.L2.global [%0], %1;" :: "l"(p.x + (size_t)u * TILE_BYTES), "r"(min(NT, p.ntok - u * NT) * (D * 2)) : "memory");
                    }
                    if (!HELPER && lane == 0 && j >= NSLOT - 1) drawn = atomicInc(&g_ticket, ntiles - p.ncl * (NSLOT - 1) - 1);
                    if (++s == NSLOT) { s = 0; ph ^= 1; }
                }
            }
        } else {
            const int g = warp - 13;
            const uint32_t rempty = HELPER ? bar_empty : mapa(bar_empty, 0);
            if (g == 0 && lane == 0) { sts32(sb + OFF_EPOCH + 8, epoch); mbar_arrive(sb + OFF_EPOCH); }
            mbar_wait(bar_full, 0);
            uint32_t t = lds32v(tk), ph = 0;
            int s = 0, nheld = 0, nout = 0, hnext = p.nh == 0 ? -1 : p.jh;
            const int nh = p.nh + (g == 0);
            uint32_t held[NH + 1];
            auto store = [&](int buf, uint32_t tile) {
                asm volatile("cp.async.bulk.tensor.2d.global.shared::cta.bulk_group.L2::cache_hint [%0, {%2, %3}], [%1], %4;"
                             :: "l"(&tmo), "r"(sb + OFF_STG + (buf * 3 + g) * STG_BYTES), "r"((g * 3 + rank) * 64), "r"((place<HELPER>(p, tile)) * NT), "l"(pol) : "memory");
            };
            auto release = [&]() {
#pragma unroll
                for (int k = 0; k <= NH; k++) if (k >= nout && k < nheld && lane == 0) store(1 + k, held[k]);
                nout = nheld;
            };
            for (int i = 0;; i++) {
                bar_sync(BAR_SFULL + g, 160);
                const int s1 = s + 1 == NSLOT ? 0 : s + 1;
                if (s1 == 0) ph ^= 1;
                if (lane == 0 && g < 2) { if (HELPER) mbar_arrive(bar_empty + 8 * s); else mbar_arrive_cluster(rempty + 8 * s); }
                const bool ready = __all_sync(~0u, mbar_test(bar_full + 8 * s1, ph));
                if (ready) bar_arrive(BAR_G + g, 288);
                if (lane == 0) {
                    asm volatile("fence.proxy.async.shared::cta;" ::: "memory");
                    if (i != hnext) store(0, t);
                    asm volatile("cp.async.bulk.commit_group;" ::: "memory");
                    if (g == 2 && i == 0 && atomicInc(&g_passed, p.nctas - 1) == (uint32_t)p.nctas - 1) atomicAdd(&g_epoch, 1);
                }
                __syncwarp();
                if (i == hnext) {
#pragma unroll
                    for (int k = 0; k <= NH; k++) if (k == nheld) held[k] = t;
                    hnext = ++nheld < nh ? hnext + p.jd : -1;
                }
                s = s1;
                if (!ready) { mbar_wait(bar_full + 8 * s, ph); bar_arrive(BAR_G + g, 288); }
                t = lds32v(tk + (((i + 1) & 7) << 2));
                if (t >= (uint32_t)p.rel && nout < nheld) { release(); if (lane == 0) asm volatile("cp.async.bulk.commit_group;" ::: "memory"); }
                if (lane == 0) asm volatile("cp.async.bulk.wait_group.read 0;" ::: "memory");
                __syncwarp();
                if (t == NO_TILE) break;
                bar_arrive(BAR_SEMPTY + g, 160);
            }
        }
        __syncwarp();
        if (!HELPER) asm volatile("barrier.cluster.arrive.relaxed.aligned;\nbarrier.cluster.wait.aligned;" ::: "memory");
    } else {
        asm volatile("setmaxnreg.inc.sync.aligned.u32 160;");
        const int wg = warp >> 2, r = lane >> 2, q = lane & 3;
        uint32_t epoch;
        if (HELPER) asm volatile("bar.sync 0;" ::: "memory");
        else {
            int prb = cid;
            asm volatile("barrier.cluster.arrive.relaxed.aligned;" ::: "memory");
            if (prb >= 36) asm volatile("barrier.cluster.wait.aligned;" ::: "memory");
#pragma unroll 1
            for (int round = 0; prb < 36; prb += p.ncl, round++) {
                const uint32_t wsm = sb + OFF_WST, msk = sb + OFF_MSK + (round & 1) * 144, mbar = sb + OFF_MBAR + (round & 1) * 8;
                if (round) {
                    bar_sync(3, 384);
                    if (tid == 0) mbar_expect_tx(mbar, 36 * 4);
                    prep_load(prb);
                }
                const uint32_t tk2 = min2(min2(tie_key(wv[0].x, wv[1].x, wv[2].x, wv[3].x), tie_key(wv[0].y, wv[1].y, wv[2].y, wv[3].y)),
                                          min2(tie_key(wv[0].z, wv[1].z, wv[2].z, wv[3].z), tie_key(wv[0].w, wv[1].w, wv[2].w, wv[3].w)));
                const uint32_t mk = __ballot_sync(~0u, (tk2 & 0xFFFFu) == 0 || tk2 < 0x10000u);
                if (round == 0) asm volatile("barrier.cluster.wait.aligned;" ::: "memory");
                if (lane < CL) st_async(mapa(msk + (rank * 12 + warp) * 4, lane), mk, mapa(mbar, lane));
#pragma unroll
                for (int j = 0; j < 4; j++) {
                    const int row = wrow + j;
                    const uint32_t ad = wsm + row * 128 + (((lane >> 2) ^ ((row & 1) | ((row >> 1) & 6))) << 4);
                    asm volatile("st.shared.v4.b32 [%0], {%1,%2,%3,%4};" :: "r"(ad), "r"(wv[j].x), "r"(wv[j].y), "r"(wv[j].z), "r"(wv[j].w) : "memory");
                }
                if (warp >= 6) bar_arrive(1, 384);
                else {
                    bar_sync(1, 384);
                    mbar_wait(sb + OFF_EPOCH, 0);
                    epoch = lds32v(sb + OFF_EPOCH + 8);
                    uint8_t* const scr = (uint8_t*)p.scr + (epoch & 1) * SCR_END;
                    mbar_wait(mbar, (round >> 1) & 1);
                    uint32_t m0 = 0, m1 = 0;
                    if (lane < KSTEPS) asm volatile("ld.volatile.shared.v2.b32 {%0,%1}, [%2];" : "=r"(m0), "=r"(m1) : "r"(msk + 8 * lane) : "memory");
                    uint32_t c0 = m0 - ((m0 >> 1) & 0x55555555u), c1 = m1 - ((m1 >> 1) & 0x55555555u);
                    c0 = (c0 & 0x33333333u) + ((c0 >> 2) & 0x33333333u) + (c1 & 0x33333333u) + ((c1 >> 2) & 0x33333333u);
                    c1 = __reduce_add_sync(~0u, (c0 >> 4) & 0x0F0F0F0Fu); c0 = __reduce_add_sync(~0u, c0 & 0x0F0F0F0Fu);
                    auto key = [&](int v) { return ((((v & 1) ? c1 : c0) >> (4 * (v & 6))) & 0xFFu) * 8 + v; };
                    const uint32_t ku = key(lane & 7);
                    const uint32_t l0 = __ballot_sync(~0u, key(lane >> 3) < ku), l1 = __ballot_sync(~0u, key(4 + (lane >> 3)) < ku);
                    const int rk = __popc((l0 >> (lane & 7)) & 0x01010101u) + __popc((l1 >> (lane & 7)) & 0x01010101u);
                    const int pp = prb & 3;
                    const int ulo = __ffs(__ballot_sync(~0u, rk == pp)) - 1, uhi = __ffs(__ballot_sync(~0u, rk == 7 - pp)) - 1;
                    uint32_t lo[4], hi[4];
                    load_unit(wsm, warp, ulo, lane, lo); load_unit(wsm, warp, uhi, lane, hi);
                    const uint32_t mm = (((m0 >> (4 * ulo)) | (m0 >> (4 * uhi))) & 15u) | ((((m1 >> (4 * ulo)) | (m1 >> (4 * uhi))) & 15u) << 4);
                    const uint2 bias2 = make_uint2(__shfl_sync(~0u, ulo < 4 ? b0 : b1, (ulo * 8 + r) & 31) * 0x10001u, __shfl_sync(~0u, uhi < 4 ? b0 : b1, (uhi * 8 + r) & 31) * 0x10001u);
                    emit_step(lo, hi, mm, prb, rank * 6 + warp, lane, ulo | (uhi << 4), bias2, scr, p.over, epoch + 1);
                }
            }
            if (cid >= 36 || warp >= 6) { mbar_wait(sb + OFF_EPOCH, 0); epoch = lds32v(sb + OFF_EPOCH + 8); }
            if (warp >= 6) for (int i = blockIdx.x * 192 + tid - 192; i < SCR_END / 16; i += gridDim.x * 192) p.scr[(~epoch & 1) * (SCR_END / 16) + i] = make_uint4(0, 0, 0, 0);
        }
        if (HELPER) { mbar_wait(sb + OFF_EPOCH, 0); epoch = lds32v(sb + OFF_EPOCH + 8); }
        if (wg == 2) bar_arrive(BAR_T, 256);
        const int mt = wg * 3 + rank, rb = mt * 4 + (warp & 3);
        const uint8_t* const scr = (const uint8_t*)p.scr + (epoch & 1) * SCR_END + mt * BLK;
        const int fo = (warp & 3) * 512 + lane * 16, io = BLK_I + (warp & 3) * 128 + r * 16, sl = (r >> 1) * 8 + q * 2 + (r & 1), so = BLK_S + (warp & 3) * 2560 + sl * 16;
        const int mo = BLK_M + ((warp & 3) * KSTEPS + (q >> 1)) * 64 + r * 8 + (q & 1) * 4;
        if (!HELPER && cid < 36) bar_sync(2, 384);
        const uint32_t blk = sb + blk_off(wg);
        if (warp == 0) {
            if (HELPER || cid >= 36 || p.ncl < 36) for (int n = 0; __any_sync(~0u, ld32(scr + 17 * 2048 + fo) == 0); n++) fail_if(n > (1 << 22));
            if (lane < 3) {
                mbar_expect_tx(sb + OFF_FB + 8 * lane, BLK);
                asm volatile("cp.async.bulk.shared::cluster.global.mbarrier::complete_tx::bytes [%0], [%1], %2, [%3];"
                             :: "r"(sb + blk_off(lane)), "l"(scr + lane * 3 * BLK), "r"(BLK), "r"(sb + OFF_FB + 8 * lane) : "memory");
            }
        }
        uint32_t a[KSTEPS][4], meta[9];
        uint2 rv[5]; uint32_t ro[5];
        uint32_t info, bias_lo, bias_hi;
        {
            const uint8_t* const fp = scr + fo; const uint8_t* const ip = scr + io; const uint8_t* const sp = scr + so; const uint8_t* const mp = scr + mo;
            mbar_wait(sb + OFF_FB + 8 * wg, 0);
            uint4 i0 = lds128(blk + io), sv[5];
#pragma unroll
            for (int j = 0; j < 5; j++) sv[j] = lds128(blk + so + j * 512);
#pragma unroll
            for (int j = 0; j < 9; j++) meta[j] = lds32(blk + mo + j * 128);
#pragma unroll
            for (int k = 0; k < KSTEPS; k++) { const uint4 v = lds128(blk + fo + k * 2048); a[k][0] = v.x; a[k][1] = v.y; a[k][2] = v.z; a[k][3] = v.w; }
            for (int n = 0;; n++) {
                uint32_t lo = __vimin3_u32(__vimin3_u32(i0.x, meta[8], sv[0].z), sv[1].z, __vimin3_u32(sv[2].z, sv[3].z, sv[4].z));
#pragma unroll
                for (int j = 0; j < 8; j += 2) lo = __vimin3_u32(lo, meta[j], meta[j + 1]);
#pragma unroll
                for (int k = 0; k < KSTEPS; k += 2) lo = __vimin3_u32(lo, a[k][0], a[k + 1][0]);
                if (__all_sync(~0u, lo != 0)) break;
                fail_if(n > (1 << 20));
                ld128_if(i0.x == 0, ip, i0.x, i0.y, i0.z, i0.w);
#pragma unroll
                for (int j = 0; j < 5; j++) ld128_if(sv[j].z == 0, sp + j * 512, sv[j].x, sv[j].y, sv[j].z, sv[j].w);
#pragma unroll
                for (int j = 0; j < 9; j++) ld32_if(meta[j] == 0, mp + j * 128, meta[j]);
#pragma unroll
                for (int k = 0; k < KSTEPS; k++) ld128_if(a[k][0] == 0, fp + k * 2048, a[k][0], a[k][1], a[k][2], a[k][3]);
            }
            info = i0.x; bias_lo = i0.y; bias_hi = i0.z;
#pragma unroll
            for (int j = 0; j < 5; j++) { rv[j] = make_uint2(sv[j].x, sv[j].y); ro[j] = sv[j].z; }
        }
#pragma unroll
        for (int j = 0; j < 4; j++) { rv[j].x ^= p.zero; rv[j].y ^= p.zero; }
        if ((wg || !BLK_FITS) && lane == 0) { if (HELPER) mbar_arrive(sb + OFF_GO + 8 * wg); else mbar_arrive_cluster(mapa(sb + OFF_GO + 8 * wg, 0)); }
        info = __shfl_sync(~0u, info, 0);
        const int ngrp = info & 0xFF, ulo = (info >> 8) & 7, uhi = (info >> 12) & 7;
#pragma unroll 1
        for (int j = 5; j < ngrp; j++)
            for (int n = 0; __any_sync(~0u, ld128(p.over + (rb * 36 + j) * 32 + sl).w != epoch + 1); n++) fail_if(n > (1 << 20));
        mbar_wait(bar_full, 0);
        const uint32_t stg = sb + OFF_STG + wg * STG_BYTES + ((lane >> 4) * 8 + (lane & 7)) * 128 + (((((lane >> 3) & 1) ? uhi : ulo) ^ (lane & 7)) << 4);
        float acc[NACC];
        uint32_t bq[NB][2], b4[NB];
        auto gather = [&](uint32_t xb) {
#pragma unroll
            for (int j = 0; j < 3; j++)
#pragma unroll
                for (int n = 0; n < NB; n++) { const uint32_t v = lds32(xb + ro[j] + (n * 9216 - RO_BIAS)); if (j < 2) acc[4 * n + j] = __uint_as_float(v); else bq[n][0] = v; }
            if (ngrp > 3) {
#pragma unroll
                for (int n = 0; n < NB; n++) bq[n][1] = lds32(xb + ro[3] + (n * 9216 - RO_BIAS));
                if (ngrp > 4) {
#pragma unroll
                    for (int n = 0; n < NB; n++) b4[n] = lds32(xb + ro[4] + (n * 9216 - RO_BIAS));
                }
            }
        };
        const int me = tid >> 7, nxt = __shfl_sync(~0u, BAR_T + (me == 2 ? 0 : me + 1), 0), prv = __shfl_sync(~0u, BAR_G + (me == 0 ? 2 : me - 1), 0);
#pragma unroll
        for (int n = 0; n < NB; n++) b4[n] = bq[n][1] = 0;
        gather(sb + OFF_X);
        bar_sync(BAR_T + wg, 256);
        auto bdesc = [](uint32_t x) { return ((uint64_t)1 << 62) | ((uint64_t)(9216 >> 4) << 32) | ((uint64_t)1 << 16) | (uint64_t)(x >> 4); };
        uint32_t xb = sb + OFF_X;
        uint64_t desc = bdesc(xb);
        const uint32_t re0 = HELPER ? bar_empty : mapa(bar_empty, 0);
        uint32_t re = re0;
        const bool releases = tid >= 256 && lane == 0;
        int hnext = p.nh == 0 ? -1 : p.jh, hbuf = 3 * STG_BYTES;
        bool more = true;
        for (int i = 0; more; i++) {
            auto rows03 = [&]() {
#pragma unroll
                for (int n = 0; n < NB; n++) mma_k16(acc + 4 * n, rv[0], rv[1], __float_as_uint(acc[4 * n]), __float_as_uint(acc[4 * n + 1]), 0.f, 0.f, 0.f, 0.f);
#pragma unroll
                for (int n = 0; n < NB; n++) mma_k16(acc + 4 * n, rv[2], rv[3], bq[n][0], bq[n][1], acc[4 * n], acc[4 * n + 1], acc[4 * n + 2], acc[4 * n + 3]);
            };
            if (ngrp <= 4) rows03();
            else {
                rows03();
#pragma unroll
                for (int n = 0; n < NB; n++) mma_k8(acc + 4 * n, rv[4], b4[n]);
#pragma unroll 1
                for (int j = 5; j < ngrp; j++) {
                    const uint4 o = __ldca(p.over + (rb * 36 + j) * 32 + sl);
#pragma unroll
                    for (int n = 0; n < NB; n++) b4[n] = lds32(xb + o.z + (n * 9216 - RO_BIAS));
#pragma unroll
                    for (int n = 0; n < NB; n++) mma_k8(acc + 4 * n, make_uint2(o.x, o.y), b4[n]);
                }
            }
            asm volatile("wgmma.fence.sync.aligned;" ::: "memory");
#pragma unroll
            for (int k = 0; k < KSTEPS; k++) {
                const uint64_t d = desc + (uint64_t)(((k >> 1) * 1024 + (k & 1) * 64) >> 4);
                if (k & 1) wgmma_sp<1>(acc, a[k], d, meta[k >> 1]);
                else       wgmma_sp<0>(acc, a[k], d, meta[k >> 1]);
                if (k == SPLIT - 1) asm volatile("wgmma.commit_group.sync.aligned;" ::: "memory");
            }
            asm volatile("wgmma.commit_group.sync.aligned;" ::: "memory");
            bar_arrive(nxt, 256);
            xb = xb == sb + OFF_X + (NSLOT - 1) * TILE_BYTES ? sb + OFF_X : xb + TILE_BYTES;
            desc = bdesc(xb);
            uint32_t sq = stg;
            if (i == hnext) { sq += hbuf; hbuf += 3 * STG_BYTES; hnext = hbuf <= (p.nh + (wg == 0)) * 3 * STG_BYTES ? hnext + p.jd : -1; }
            asm volatile("wgmma.wait_group.sync.aligned 1;" ::: "memory");
            if (wg != 0 || i != 0) bar_arrive(prv, 288);
            if (i != 0) bar_sync(BAR_SEMPTY + me, 160);
            asm volatile("wgmma.wait_group.sync.aligned 0;" ::: "memory");
            if (releases) { if (HELPER) mbar_arrive(re); else mbar_arrive_cluster(re); }
            re = re == re0 + 8 * (NSLOT - 1) ? re0 : re + 8;
#pragma unroll
            for (int n = 0; n + 1 < NB; n += 2) {
                const uint32_t p0 = pack_bias(acc[4 * n], acc[4 * n + 1], bias_lo), p1 = pack_bias(acc[4 * n + 2], acc[4 * n + 3], bias_hi);
                const uint32_t p2 = pack_bias(acc[4 * n + 4], acc[4 * n + 5], bias_lo), p3 = pack_bias(acc[4 * n + 6], acc[4 * n + 7], bias_hi);
                asm volatile("stmatrix.sync.aligned.m8n8.x4.trans.shared.b16 [%0], {%1,%2,%3,%4};" :: "r"(sq + n * 1024), "r"(p0), "r"(p1), "r"(p2), "r"(p3) : "memory");
            }
            if (NB & 1) {
                const uint32_t p0 = pack_bias(acc[NACC - 4], acc[NACC - 3], bias_lo), p1 = pack_bias(acc[NACC - 2], acc[NACC - 1], bias_hi);
                asm volatile("stmatrix.sync.aligned.m8n8.x2.trans.shared.b16 [%0], {%1,%2};" :: "r"(sq + (NB - 1) * 1024), "r"(p0), "r"(p1) : "memory");
            }
            bar_arrive(BAR_SFULL + me, 160);
            bar_sync(BAR_G + me, 288);
            const uint32_t tn = lds32v(tk + (((i + 1) & 7) << 2));
            gather(xb);
            more = __any_sync(~0u, tn != NO_TILE);
            if (more || wg == 0) bar_sync(BAR_T + me, 256);
        }
        if (wg == 0) bar_arrive(BAR_G + 2, 288);
        __syncwarp();
        if (!HELPER) asm volatile("barrier.cluster.arrive.relaxed.aligned;\nbarrier.cluster.wait.aligned;" ::: "memory");
    }
}

typedef CUresult (*EncodeFn)(CUtensorMap*, CUtensorMapDataType, cuuint32_t, void*, const cuuint64_t*, const cuuint64_t*, const cuuint32_t*, const cuuint32_t*,
                             CUtensorMapInterleave, CUtensorMapSwizzle, CUtensorMapL2promotion, CUtensorMapFloatOOBfill);

extern "C" void kernel_launch(void* const* d_in, const int* in_sizes, int n_in, void* d_out, int out_size) {
    static EncodeFn enc = nullptr;
    static int ncl = 0, nhelp = 0;
    const int ntok = in_sizes[0] / D;
    cudaLaunchConfig_t cfg = {};
    cudaLaunchAttribute at[1];
    at[0].id = cudaLaunchAttributeClusterDimension; at[0].val.clusterDim.x = CL; at[0].val.clusterDim.y = 1; at[0].val.clusterDim.z = 1;
    cfg.blockDim = dim3(NTHREADS); cfg.dynamicSmemBytes = SMEM_BYTES; cfg.attrs = at; cfg.numAttrs = 1; cfg.stream = cudaStreamPerThread;
    if (!enc) {
        cudaDriverEntryPointQueryResult qr; void* fn = nullptr;
        cudaGetDriverEntryPoint("cuTensorMapEncodeTiled", &fn, cudaEnableDefault, &qr);
        enc = (EncodeFn)fn;
        cudaFuncSetAttribute(spgemm_kernel<false>, cudaFuncAttributeMaxDynamicSharedMemorySize, SMEM_BYTES);
        cudaFuncSetAttribute(spgemm_kernel<true>, cudaFuncAttributeMaxDynamicSharedMemorySize, SMEM_BYTES);
        int dev = 0, nsm = 0;
        cudaGetDevice(&dev);
        cudaDeviceGetAttribute(&nsm, cudaDevAttrMultiProcessorCount, dev);
        cfg.gridDim = dim3(CL * (nsm / CL));
        cudaOccupancyMaxActiveClusters(&ncl, spgemm_kernel<false>, &cfg);
        if (ncl < 1) ncl = 1;
        nhelp = nsm > CL * ncl ? (nsm - CL * ncl) / CL : 0;
    }
    CUtensorMap tmx, tmo;
    {
        cuuint64_t dims[4] = {64, 8, 9, (cuuint64_t)(ntok / 8)};
        cuuint64_t strides[3] = {D * 2, 128, 8 * D * 2};
        cuuint32_t box[4] = {64, 8, 9, NB}, es[4] = {1, 1, 1, 1};
        enc(&tmx, CU_TENSOR_MAP_DATA_TYPE_BFLOAT16, 4, d_in[0], dims, strides, box, es, CU_TENSOR_MAP_INTERLEAVE_NONE,
            CU_TENSOR_MAP_SWIZZLE_128B, CU_TENSOR_MAP_L2_PROMOTION_L2_128B, CU_TENSOR_MAP_FLOAT_OOB_FILL_NONE);
    }
    {
        cuuint64_t dims[2] = {D, (cuuint64_t)ntok};
        cuuint64_t strides[1] = {D * 2};
        cuuint32_t box[2] = {64, NT}, es[2] = {1, 1};
        enc(&tmo, CU_TENSOR_MAP_DATA_TYPE_BFLOAT16, 2, d_out, dims, strides, box, es, CU_TENSOR_MAP_INTERLEAVE_NONE,
            CU_TENSOR_MAP_SWIZZLE_128B, CU_TENSOR_MAP_L2_PROMOTION_NONE, CU_TENSOR_MAP_FLOAT_OOB_FILL_NONE);
    }
    Params p;
    p.w = (const uint16_t*)d_in[1]; p.bias = (const uint16_t*)d_in[2]; p.x = (const uint8_t*)d_in[0];
    p.ntok = ntok;
    cudaGetSymbolAddress((void**)&p.scr, g_scr); cudaGetSymbolAddress((void**)&p.over, g_over);
    p.zero = 0;
    p.alltiles = (ntok + NT - 1) / NT;
    const int nc = ncl < p.alltiles ? ncl : p.alltiles;
    p.a = nhelp ? (int)(2 * nc / (nhelp * 1.07) + 0.5) : 2;
    if (p.a < 2) p.a = 2;
    const int nblk = (int)(p.alltiles / (p.a + 2) * 0.6);
    const int nh = nhelp && 2 * nblk >= nhelp && p.alltiles - 2 * nblk >= nc ? nhelp : 0;
    p.nha = nh ? 2 * nblk : 0; p.nht = p.alltiles > 16 * nc ? nh : 0;
    p.ntiles = p.alltiles - p.nha - p.nht;
    p.trig = p.ntiles - nc * NSLOT - 30;
    p.nfull = nh ? nblk * p.a : 0; p.amagic = (int)(0xFFFFFFFFu / (uint32_t)p.a + 1);
    p.ncl = nc; p.nctas = CL * (nc + nh);
    p.nh = (int)NH; p.jh = 4; p.jd = 4; p.rel = p.ntiles - 50;
    auto tiles = [](double v) { return (int)(v * 56 / NT); };
    auto ns = [](double v) { return (int)(v * NT / 56); };
    p.pfd = 1500; p.pk = ns(600);
    p.ta = (int)(p.ntiles * 0.33) + 1; p.lead1 = tiles(290); p.pw = 2750;
    p.k1 = tiles(68); p.pfs = ns(700); p.pfs2 = ns(1950);
    p.te = p.ntiles + 2; p.leade = tiles(45); p.slope1 = ((p.lead1 - p.leade) << 16) / (p.te - p.ta);
    cfg.gridDim = dim3(CL * nc);
    cudaLaunchKernelEx(&cfg, spgemm_kernel<false>, tmx, tmo, p);
    if (nh) {
        at[0].id = cudaLaunchAttributeProgrammaticStreamSerialization; at[0].val.programmaticStreamSerializationAllowed = 1;
        cfg.gridDim = dim3(CL * nh);
        p.ncl = nh;
        p.nh = p.nht ? NH : 0; p.jh = p.nha / nh - 10; p.jd = 1; p.rel = p.nha;
        cudaLaunchKernelEx(&cfg, spgemm_kernel<true>, tmx, tmo, p);
    }
}
```

```cpp
#include <cuda_runtime.h>
#include <cuda_bf16.h>
#include <cuda.h>
#include <stdint.h>

constexpr int D = 576;
constexpr int NH = 2;
constexpr int NT = 48;
constexpr int NSLOT = 3;
constexpr int SPLIT = 13;
constexpr int KSTEPS = 18;
constexpr int CL = 3;
constexpr int TILE_BYTES = NT * D * 2;
constexpr int STG_BYTES = NT * 128;
constexpr int NACC = NT / 2;
constexpr int NB = NT / 8;
constexpr int NCONS = 384;
constexpr int NTHREADS = 512;
constexpr uint32_t NO_TILE = 0xFFFFFFFFu;

constexpr int OFF_X = 0;
constexpr int OFF_STG = OFF_X + NSLOT * TILE_BYTES;
constexpr int OFF_WST = OFF_STG;
constexpr int OFF_FULL = OFF_STG + ((1 + NH) * 3 + 1) * STG_BYTES;
constexpr int OFF_EMPTY = OFF_FULL + 8 * NSLOT;
constexpr int OFF_MBAR = OFF_EMPTY + 8 * NSLOT;
constexpr int OFF_GO = OFF_MBAR + 16;
constexpr int OFF_FB = OFF_GO + 24;
constexpr int OFF_EPOCH = OFF_FB + 24;
constexpr int OFF_TK = OFF_EPOCH + 16;
constexpr int OFF_MSK = OFF_TK + 32;
constexpr int SMEM_BYTES = OFF_MSK + 2 * 36 * 4 + 1024;
static_assert(SMEM_BYTES <= 232448 && NSLOT < 8 && NSLOT >= 3, "layout");
constexpr int BAR_T = 4, BAR_SFULL = 7, BAR_SEMPTY = 10, BAR_G = 13;

constexpr int BLK_M = KSTEPS * 2048, BLK_S = BLK_M + 4 * KSTEPS * 64, BLK_I = BLK_S + 4 * 2560, BLK = BLK_I + 4 * 128, SCR_END = 9 * BLK;
constexpr bool BLK_FITS = BLK <= TILE_BYTES && BLK <= OFF_FULL - OFF_STG;
__host__ __device__ constexpr int blk_off(int g) { return BLK_FITS ? (g == 0 ? OFF_STG : OFF_X + g * TILE_BYTES) : OFF_X + TILE_BYTES + (g + 2) % 3 * BLK; }
static_assert(blk_off(0) + BLK <= OFF_FULL && blk_off(2) + BLK <= OFF_STG && OFF_WST + 192 * 128 <= OFF_FULL, "fragment blocks");
__device__ __align__(128) uint4    g_scr[2][SCR_END / 16];
__device__ __align__(128) uint4    g_over[36 * 144 * 8];
__device__ __align__(128) uint32_t g_epoch;
__device__ __align__(128) uint32_t g_passed;
__device__ __align__(128) uint32_t g_ticket;

__device__ __forceinline__ uint32_t now() { uint32_t c; asm volatile("mov.u32 %0, %%globaltimer_lo;" : "=r"(c)); return c; }
__device__ __forceinline__ void wait_until(uint32_t due) { while ((int)(now() - due) < 0) __nanosleep(20); }

__device__ __forceinline__ uint32_t max2(uint32_t a, uint32_t b) { uint32_t d; asm("max.u16x2 %0, %1, %2;" : "=r"(d) : "r"(a), "r"(b)); return d; }
__device__ __forceinline__ uint32_t min2(uint32_t a, uint32_t b) { uint32_t d; asm("min.u16x2 %0, %1, %2;" : "=r"(d) : "r"(a), "r"(b)); return d; }
__device__ __forceinline__ uint32_t sign2(uint32_t a) { uint32_t d; asm("prmt.b32 %0, %1, %1, 0xBB99;" : "=r"(d) : "r"(a)); return d; }
__device__ __forceinline__ void zip4(uint32_t a01, uint32_t a23, uint32_t b01, uint32_t b23, uint32_t (&x)[4]) {
    x[0] = __byte_perm(a01, b01, 0x5410); x[1] = __byte_perm(a01, b01, 0x7632); x[2] = __byte_perm(a23, b23, 0x5410); x[3] = __byte_perm(a23, b23, 0x7632);
}
__device__ __forceinline__ void middle2(const uint32_t (&x)[4], uint32_t (&m)[4], uint32_t& u, uint32_t& v) {
#pragma unroll
    for (int i = 0; i < 4; i++) m[i] = x[i] & 0x7FFF7FFFu;
    u = min2(max2(m[0], m[1]), max2(m[2], m[3])); v = max2(min2(m[0], m[1]), min2(m[2], m[3]));
}
__device__ __forceinline__ uint32_t tie_key(uint32_t x0, uint32_t x1, uint32_t x2, uint32_t x3) {
    const uint32_t x[4] = {x0, x1, x2, x3};
    uint32_t m[4], u, v;
    middle2(x, m, u, v);
    return max2(u, 0x00010001u) ^ v;
}
__device__ __forceinline__ void load_unit(uint32_t wsm, int ls, int unit, int lane, uint32_t (&m)[4]) {
    const int row = ls * 32 + (lane >> 4) * 16 + ((lane & 7) >> 1) * 4 + ((lane >> 3) & 1) * 2 + (lane & 1);
    const uint32_t ad = wsm + row * 128 + ((unit ^ ((row & 1) | ((row >> 1) & 6))) << 4);
    asm volatile("ldmatrix.sync.aligned.m8n8.x4.trans.shared.b16 {%0,%1,%2,%3}, [%4];" : "=r"(m[0]), "=r"(m[1]), "=r"(m[2]), "=r"(m[3]) : "r"(ad) : "memory");
}
__device__ __forceinline__ void split_pair(const uint32_t (&x)[4], bool P, uint32_t& alo, uint32_t& ahi, uint32_t& nib, uint32_t& rlo, uint32_t& rhi) {
    uint32_t m[4], u, v;
    middle2(x, m, u, v);
    const uint32_t c = 0x80008000u - max2(max2(u, v), 0x00010001u);
    uint32_t k0 = sign2(m[0] + c), k1 = sign2(m[1] + c), k2 = sign2(m[2] + c), k3 = sign2(m[3] + c);
    const uint32_t three = (k0 & k1 & (k2 | k3)) | (k2 & k3 & (k0 | k1)), four = k0 & k1 & k2 & k3;
    const uint32_t pa = P ? k2 : k0, pb = P ? k3 : k1;
    const uint32_t ra = three & pa, rb = three & pb & (four | ~pa);
    const uint32_t va = (P ? x[2] : x[0]) & ra, vb = (P ? x[3] : x[1]) & rb;
    if (P) { k2 &= ~ra; k3 &= ~rb; } else { k0 &= ~ra; k1 &= ~rb; }
    const uint32_t s1 = k1 & k0, s2 = k2 & (k0 | k1);
    const uint32_t t = (k1 & x[1]) | (~k1 & k2 & x[2]);
    const uint32_t x0 = (k0 & x[0]) | (~k0 & t), x1 = (s1 & x[1]) | (s2 & x[2]) | (k3 & x[3]);
    nib = (~k0 & k1 & 0x00010001u) | (~k0 & ~k1 & 0x00020002u) | (~s2 & 0x00040004u) | (~s1 & 0x00080008u);
    alo = __byte_perm(x0, x1, 0x5410); ahi = __byte_perm(x0, x1, 0x7632);
    rlo = __byte_perm(va, vb, 0x5410); rhi = __byte_perm(va, vb, 0x7632);
}
__device__ __forceinline__ uint32_t nonzero(uint32_t v) { return v ? v : 0x8000u; }
__device__ __forceinline__ void pub32(void* a, uint32_t v) { asm volatile("st.relaxed.gpu.global.u32 [%0], %1;" :: "l"(a), "r"(v) : "memory"); }
__device__ __forceinline__ void pub128(bool c, void* a, uint32_t x, uint32_t y, uint32_t z, uint32_t w) {
    asm volatile("{\n.reg .pred p;\n.reg .b64 s, t;\n.reg .b128 v;\nsetp.ne.u32 p, %5, 0;\nmov.b64 s, {%1, %2};\nmov.b64 t, {%3, %4};\nmov.b128 v, {s, t};\n@p st.relaxed.gpu.global.b128 [%0], v;\n}\n"
                 :: "l"(a), "r"(x), "r"(y), "r"(z), "r"(w), "r"((uint32_t)c) : "memory");
}
constexpr int RO_BIAS = 16;
__device__ __forceinline__ uint32_t resid_off(int g, int P, int r) {
    int k0 = 4 * g + 2 * P;
    int chunk = k0 >> 6, byte = (k0 & 63) * 2;
    return chunk * 1024 + r * 128 + (((byte >> 4) ^ r) << 4) + (byte & 15);
}
__device__ __forceinline__ void emit_step(const uint32_t (&lo)[4], const uint32_t (&hi)[4], uint32_t mm, int rb, int ks, int lane, uint32_t units, uint2 bias2,
                                          uint8_t* scr, uint4* over, uint32_t tag) {
    scr += (rb >> 2) * BLK;
    const int wp = rb & 3;
    const int lo16 = (lane >> 3) * 128 + ((lane >> 2) & 1) * 16;
    uint8_t* const s0 = scr + BLK_S + wp * 2560 + lo16;
    uint8_t* const s1 = (uint8_t*)(over + rb * 144 * 8) + lo16;
    auto put_slot = [&](bool c, int sl, uint32_t v0, uint32_t v1, uint32_t off) {
        pub128(c, (sl < 20 ? s0 : s1) + (sl >> 2) * 512 + (sl & 3) * 32, v0, v1, off + RO_BIAS, tag);
    };
    const int r = lane >> 2, q = lane & 3, g0 = ks * 8 + q, g1 = g0 + 4;
    const uint32_t gm = __shfl_sync(~0u, mm, ks);
    const uint32_t c2 = __popc(mm & 0x55u) | (__popc(mm & 0xAAu) << 16);
    const uint32_t tot = __reduce_add_sync(~0u, c2), pre = __reduce_add_sync(~0u, lane < ks ? c2 : 0u);
    const int ne = tot & 0xFFFF, no = tot >> 16;
    const uint32_t par = (q & 1) ? 0xAAu : 0x55u;
    const int base = (q & 1) ? pre >> 16 : pre & 0xFFFF;
    const int rk0 = base + __popc(gm & par & ((1u << q) - 1)), rk1 = base + __popc(gm & par & ((16u << q) - 1));
    uint32_t a[4], rs[4], x[4], w0, w1;
    zip4(lo[0], lo[1], hi[0], hi[1], x); split_pair(x, rk0 & 1, a[0], a[1], w0, rs[0], rs[1]);
    zip4(lo[2], lo[3], hi[2], hi[3], x); split_pair(x, rk1 & 1, a[2], a[3], w1, rs[2], rs[3]);
    pub128(true, scr + ks * 2048 + wp * 512 + lane * 16, nonzero(a[0]), a[1], a[2], a[3]);
    w0 <<= 4 * q; w1 <<= 4 * q;
    w0 |= __shfl_xor_sync(~0u, w0, 1); w1 |= __shfl_xor_sync(~0u, w1, 1);
    w0 |= __shfl_xor_sync(~0u, w0, 2); w1 |= __shfl_xor_sync(~0u, w1, 2);
    if (q < 2) pub32(scr + BLK_M + (wp * KSTEPS + ks) * 64 + r * 8 + q * 4, q ? w1 : w0);
    const int em = min(ne, max(8, 16 - no)), om = min(no, 16 - em);
    const int odd = q & 1, m = odd ? om : em;
#pragma unroll
    for (int e = 0; e < 2; e++) {
        const int rk = e ? rk1 : rk0, t = 15 - rk;
        const int u = min(rk, t), in = (u >> 1) * 4 + (u & 1) + 2 * (odd ^ (rk >> 3 & 1)), out = 16 + (odd ? ne - em : 0) + rk - m;
        const int sl = rk >= m ? out : in;
        put_slot((gm >> (4 * e + q)) & 1, sl, rs[2 * e], rs[2 * e + 1], resid_off(e ? g1 : g0, rk & 1, r));
    }
    const int ntot = ne + no;
    const int ng = ntot > 16 ? (ntot + 3) >> 2 : min(4, (max(ne, no) + 1) >> 1);
    pub128(ks == 7 && q == 0, scr + BLK_I + wp * 128 + r * 16, ng | (units << 8), bias2.x, bias2.y, 0);
    const int idx = 2 * ks + (q & 1);
    const int frow = ks < 5 ? ks : ng - 1;
    const bool fill = ks < 4 ? !(idx < ((q >> 1) ? om : em) || (15 - idx) < ((q >> 1) ? em : om)) : (ks == 4 || (ks == 5 && ng > 5)) && 4 * frow + q >= ntot;
    put_slot(fill, frow * 4 + q, 0, 0, resid_off(q >> 1, q & 1, r));
}

template<int SEL> __device__ __forceinline__ void wgmma_sp(float (&d)[NACC], const uint32_t (&a)[4], uint64_t bdesc, uint32_t meta) {
    asm volatile("wgmma.mma_async.sp.sync.aligned.m64n48k32.f32.bf16.bf16 {%0, %1, %2, %3, %4, %5, %6, %7, %8, %9, %10, %11, %12, %13, %14, %15, %16, %17, %18, %19, %20, %21, %22, %23}, {%24, %25, %26, %27}, %28, %29, %30, 1, 1, 1, 0;"
        : "+f"(d[0]), "+f"(d[1]), "+f"(d[2]), "+f"(d[3]), "+f"(d[4]), "+f"(d[5]), "+f"(d[6]), "+f"(d[7]), "+f"(d[8]), "+f"(d[9]), "+f"(d[10]), "+f"(d[11]), "+f"(d[12]), "+f"(d[13]), "+f"(d[14]), "+f"(d[15]), "+f"(d[16]), "+f"(d[17]), "+f"(d[18]), "+f"(d[19]), "+f"(d[20]), "+f"(d[21]), "+f"(d[22]), "+f"(d[23])
        : "r"(a[0]), "r"(a[1]), "r"(a[2]), "r"(a[3]), "l"(bdesc), "r"(meta), "n"(SEL));
}
__device__ __forceinline__ void bar_sync(int id, int n) { asm volatile("bar.sync %0, %1;" :: "r"(id), "r"(n) : "memory"); }
__device__ __forceinline__ void bar_arrive(int id, int n) { asm volatile("bar.arrive %0, %1;" :: "r"(id), "r"(n) : "memory"); }

__device__ __forceinline__ void mbar_init(uint32_t bar, uint32_t cnt) { asm volatile("mbarrier.init.shared::cta.b64 [%0], %1;" :: "r"(bar), "r"(cnt) : "memory"); }
__device__ __forceinline__ void mbar_expect_tx(uint32_t bar, uint32_t bytes) {
    asm volatile("mbarrier.arrive.expect_tx.shared::cta.b64 _, [%0], %1;" :: "r"(bar), "r"(bytes) : "memory");
}
__device__ __forceinline__ void mbar_arrive(uint32_t bar) { asm volatile("mbarrier.arrive.shared::cta.b64 _, [%0];" :: "r"(bar) : "memory"); }
__device__ __forceinline__ void mbar_arrive_cluster(uint32_t bar) { asm volatile("mbarrier.arrive.shared::cluster.b64 _, [%0];" :: "r"(bar) : "memory"); }
__device__ __forceinline__ bool mbar_try(uint32_t bar, uint32_t parity) {
    uint32_t ok;
    asm volatile("{\n.reg .pred p;\nmbarrier.try_wait.parity.shared::cta.b64 p, [%1], %2;\nselp.u32 %0, 1, 0, p;\n}\n" : "=r"(ok) : "r"(bar), "r"(parity) : "memory");
    return ok;
}
__device__ __forceinline__ bool mbar_test(uint32_t bar, uint32_t parity) {
    uint32_t ok;
    asm volatile("{\n.reg .pred p;\nmbarrier.test_wait.parity.shared::cta.b64 p, [%1], %2;\nselp.u32 %0, 1, 0, p;\n}\n" : "=r"(ok) : "r"(bar), "r"(parity) : "memory");
    return ok;
}
__device__ __forceinline__ void fail_if(bool c) { asm volatile("{\n.reg .pred p;\nsetp.ne.u32 p, %0, 0;\n@p st.volatile.global.u32 [%1], %0;\n}\n" :: "r"((uint32_t)c), "l"(0ull) : "memory"); }
__device__ __forceinline__ void mbar_wait(uint32_t bar, uint32_t parity) {
    int n = 0;
    while (!mbar_try(bar, parity)) fail_if(++n > (1 << 20));
}
__device__ __forceinline__ void st_async(uint32_t addr, uint32_t v, uint32_t bar) {
    asm volatile("st.async.weak.shared::cluster.mbarrier::complete_tx::bytes.u32 [%0], %1, [%2];" :: "r"(addr), "r"(v), "r"(bar) : "memory");
}
__device__ __forceinline__ uint32_t mapa(uint32_t a, uint32_t cta) { uint32_t d; asm("mapa.shared::cluster.u32 %0, %1, %2;" : "=r"(d) : "r"(a), "r"(cta)); return d; }
__device__ __forceinline__ uint32_t lds32(uint32_t a) { uint32_t v; asm volatile("ld.shared.b32 %0, [%1];" : "=r"(v) : "r"(a)); return v; }
__device__ __forceinline__ uint4 lds128(uint32_t a) { uint4 v; asm volatile("ld.shared.v4.b32 {%0,%1,%2,%3}, [%4];" : "=r"(v.x), "=r"(v.y), "=r"(v.z), "=r"(v.w) : "r"(a)); return v; }
__device__ __forceinline__ uint32_t lds32v(uint32_t a) { uint32_t v; asm volatile("ld.volatile.shared.b32 %0, [%1];" : "=r"(v) : "r"(a) : "memory"); return v; }
__device__ __forceinline__ void sts32(uint32_t a, uint32_t v) { asm volatile("st.shared.b32 [%0], %1;" :: "r"(a), "r"(v) : "memory"); }
__device__ __forceinline__ uint32_t ld32(const void* a) { uint32_t v; asm volatile("ld.relaxed.gpu.global.u32 %0, [%1];" : "=r"(v) : "l"(a) : "memory"); return v; }
__device__ __forceinline__ uint4 ld128(const void* a) {
    uint4 v;
    asm volatile("{\n.reg .b64 s, t;\n.reg .b128 v;\nld.relaxed.gpu.global.L1::no_allocate.b128 v, [%4];\nmov.b128 {s, t}, v;\nmov.b64 {%0, %1}, s;\nmov.b64 {%2, %3}, t;\n}\n"
                 : "=r"(v.x), "=r"(v.y), "=r"(v.z), "=r"(v.w) : "l"(a) : "memory");
    return v;
}
__device__ __forceinline__ void ld128_if(bool c, const void* a, uint32_t& x, uint32_t& y, uint32_t& z, uint32_t& w) {
    asm volatile("{\n.reg .pred p;\n.reg .b64 s, t;\n.reg .b128 v;\nsetp.ne.u32 p, %5, 0;\nmov.b64 s, {%0, %1};\nmov.b64 t, {%2, %3};\nmov.b128 v, {s, t};\n"
                 "@p ld.relaxed.gpu.global.L1::no_allocate.b128 v, [%4];\nmov.b128 {s, t}, v;\nmov.b64 {%0, %1}, s;\nmov.b64 {%2, %3}, t;\n}\n"
                 : "+r"(x), "+r"(y), "+r"(z), "+r"(w) : "l"(a), "r"((uint32_t)c) : "memory");
}
__device__ __forceinline__ void ld32_if(bool c, const void* a, uint32_t& x) {
    asm volatile("{\n.reg .pred p;\nsetp.ne.u32 p, %2, 0;\n@p ld.relaxed.gpu.global.u32 %0, [%1];\n}\n" : "+r"(x) : "l"(a), "r"((uint32_t)c) : "memory");
}
__device__ __forceinline__ void mma_k8(float* c, uint2 a, uint32_t b) {
    asm volatile("mma.sync.aligned.m16n8k8.row.col.f32.bf16.bf16.f32 {%0,%1,%2,%3}, {%4,%5}, {%6}, {%0,%1,%2,%3};"
                 : "+f"(c[0]), "+f"(c[1]), "+f"(c[2]), "+f"(c[3]) : "r"(a.x), "r"(a.y), "r"(b));
}
__device__ __forceinline__ void mma_k16(float* d, uint2 a, uint2 a2, uint32_t b0, uint32_t b1, float c0, float c1, float c2, float c3) {
    asm volatile("mma.sync.aligned.m16n8k16.row.col.f32.bf16.bf16.f32 {%0,%1,%2,%3}, {%4,%5,%6,%7}, {%8,%9}, {%10,%11,%12,%13};"
                 : "=f"(d[0]), "=f"(d[1]), "=f"(d[2]), "=f"(d[3]) : "r"(a.x), "r"(a.y), "r"(a2.x), "r"(a2.y), "r"(b0), "r"(b1), "f"(c0), "f"(c1), "f"(c2), "f"(c3));
}
__device__ __forceinline__ uint32_t pack_bias(float lo, float hi, uint32_t bias2) {
    uint32_t p, o;
    asm("cvt.rn.bf16x2.f32 %0, %1, %2;" : "=r"(p) : "f"(hi), "f"(lo));
    asm("add.rn.bf16x2 %0, %1, %2;" : "=r"(o) : "r"(p), "r"(bias2));
    return o;
}

struct Params {
    const uint16_t* w; const uint16_t* bias; const uint8_t* x; uint4* scr; uint4* over;
    int ntok;
    int ntiles;
    int alltiles;
    int ncl;
    int nctas;
    int pfd, pk;
    int ta, lead1, pw, k1, pfs, pfs2;
    int te, leade, slope1;
    uint32_t zero;
    int nha, nht, trig;
    int nh, jh, jm, jd, rel;
    int a, amagic, nfull;
};
template <bool HELPER> __device__ __forceinline__ int place(const Params& p, int m) {
    if (HELPER) return (m < p.nha ? (m >> 1) * (p.a + 2) + ((m & 1) ? p.a + 1 : p.a >> 1) : p.alltiles - p.nht - p.nha + m);
    const int blk = (int)(((uint64_t)min(m, p.nfull) * (uint32_t)p.amagic) >> 32), r = m - blk * p.a;
    return (m + 2 * blk + (m < p.nfull && r >= (p.a >> 1)));
}

template <bool HELPER>
__global__ void __launch_bounds__(NTHREADS, 1)
spgemm_kernel(const __grid_constant__ CUtensorMap tmx, const __grid_constant__ CUtensorMap tmo, const Params p) {
    extern __shared__ unsigned char smem_raw[];
    const uint32_t sb = ((uint32_t)__cvta_generic_to_shared(smem_raw) + 1023u) & ~1023u;
    const int tid = threadIdx.x, warp = __shfl_sync(~0u, tid >> 5, 0), lane = tid & 31;
    const uint32_t tstart = now();
    const int rank = blockIdx.x % CL, cid = blockIdx.x / CL;
    const uint32_t bar_full = sb + OFF_FULL, bar_empty = sb + OFF_EMPTY, tk = sb + OFF_TK;
    uint4 wv[4];
    const int wrow = warp * 16 + (lane & 3) * 4;
    uint32_t b0, b1;
    auto prep_load = [&](int prb) {
        const uint32_t f0 = (prb >> 2) * 64;
        const uint16_t* const pa = p.w + ((uint32_t)(rank * 192 + wrow) * D + f0 + (lane >> 2) * 8);
#pragma unroll
        for (int j = 0; j < 4; j++) wv[j] = __ldg((const uint4*)(pa + j * D));
        b0 = __ldg(p.bias + (f0 + lane)); b1 = __ldg(p.bias + (f0 + 32 + lane));
    };
    if (!HELPER && warp < 12 && cid < 36) prep_load(cid);

    if (warp >= 12) {
        asm volatile("setmaxnreg.dec.sync.aligned.u32 32;");
        uint32_t epoch = 0;
        if (tid == NCONS + 32) asm volatile("ld.relaxed.gpu.global.u32 %0, [%1];" : "=r"(epoch) : "l"(&g_epoch) : "memory");
        if (tid == NCONS) {
#pragma unroll
            for (int s = 0; s < NSLOT; s++) { mbar_init(bar_full + 8 * s, 1); mbar_init(bar_empty + 8 * s, HELPER ? 6 : 6 * CL); }
            mbar_init(sb + OFF_MBAR, 1); mbar_init(sb + OFF_MBAR + 8, 1);
            mbar_init(sb + OFF_GO, HELPER ? 4 : 4 * CL); mbar_init(sb + OFF_GO + 8, HELPER ? 4 : 4 * CL); mbar_init(sb + OFF_GO + 16, HELPER ? 4 : 4 * CL); mbar_init(sb + OFF_EPOCH, 1);
            mbar_init(sb + OFF_FB, 1); mbar_init(sb + OFF_FB + 8, 1); mbar_init(sb + OFF_FB + 16, 1);
            asm volatile("fence.mbarrier_init.release.cluster;" ::: "memory");
            mbar_expect_tx(sb + OFF_MBAR, 36 * 4);
            if (!HELPER) asm volatile("griddepcontrol.launch_dependents;");
            asm volatile("prefetch.tensormap [%0];" :: "l"(&tmo) : "memory");
            asm volatile("prefetch.tensormap [%0];" :: "l"(&tmx) : "memory");
        }
        __syncwarp();
        if (HELPER) asm volatile("bar.sync 0;" ::: "memory");
        else asm volatile("barrier.cluster.arrive.relaxed.aligned;\nbarrier.cluster.wait.aligned;" ::: "memory");
        uint64_t pol;
        asm volatile("createpolicy.fractional.L2::evict_first.b64 %0, 1.0;" : "=l"(pol));
        if (warp == 12) {
            const int ntiles = HELPER ? p.alltiles - p.ntiles : p.ntiles;
            if (!HELPER && rank != 0) {
                auto phys = [&](int m) { return m < ntiles ? place<false>(p, m) : p.alltiles - p.nht; };
                auto prefetch = [&](int t) {
                    const int rows = min(NT, p.ntok - t * NT), r0 = rows * (rank - 1) / 2, r1 = rows * rank / 2;
                    if (lane == 0 && r1 > r0)
                        asm volatile("cp.async.bulk.prefetch.L2.global [%0], %1;" :: "l"(p.x + (size_t)t * TILE_BYTES + r0 * (D * 2)), "r"((r1 - r0) * (D * 2)) : "memory");
                };
                const int u0 = phys(p.ncl), n0 = phys(NSLOT * p.ncl) - u0;
                for (int k = cid; k < n0; k += p.ncl) { wait_until(tstart + p.pfd + k * p.pk / p.ncl); prefetch(u0 + k); }
                const int ua = phys(p.ta), n1 = phys(p.ta + p.lead1) - ua;
                for (int k = cid; k < n1; k += p.ncl) { wait_until(tstart + p.pw + (min(k, p.k1) * p.pfs + max(k - p.k1, 0) * p.pfs2) / p.ncl); prefetch(ua + k); }
            } else {
                const uint32_t rtk = HELPER ? tk : mapa(tk, lane < CL ? lane : 0), rfull = HELPER ? bar_full : mapa(bar_full, lane < CL ? lane : 0);
                int s = 0; uint32_t ph = 1, drawn = 0;
                for (int j = 0;; j++) {
                    const int t = HELPER || j < NSLOT ? cid + j * p.ncl : (int)__shfl_sync(~0u, drawn, 0) + NSLOT * p.ncl;
                    const bool valid = t < ntiles;
                    const int row = (place<HELPER>(p, t) * NB) ^ p.zero;
                    if (j > 0 && j < NSLOT) {
#pragma unroll
                        for (int g = 0; g < 3; g++) if (blk_off(g) < OFF_X + (j + 1) * TILE_BYTES && blk_off(g) + BLK > OFF_X + j * TILE_BYTES) mbar_wait(sb + OFF_GO + 8 * g, 0);
                    }
                    mbar_wait(bar_empty + 8 * s, ph);
                    if (HELPER && valid && t >= p.nha) {
                        for (int n = 0; ld32(&g_ticket) - 1 < (uint32_t)p.trig; n++) { __nanosleep(200); fail_if(n > (1 << 22)); }
                    }
                    if (valid && lane == 0) {
                        if (HELPER)
                            asm volatile("cp.async.bulk.tensor.4d.shared::cluster.global.mbarrier::complete_tx::bytes.L2::cache_hint [%0], [%1, {%3, %3, %3, %4}], [%2], %5;"
                                         :: "r"(sb + OFF_X + s * TILE_BYTES), "l"(&tmx), "r"(bar_full + 8 * s), "r"(0), "r"(row), "l"(pol) : "memory");
                        else
                            asm volatile("cp.async.bulk.tensor.4d.shared::cluster.global.mbarrier::complete_tx::bytes.multicast::cluster.L2::cache_hint [%0], [%1, {%3, %3, %3, %4}], [%2], %5, %6;"
                                         :: "r"(sb + OFF_X + s * TILE_BYTES), "l"(&tmx), "r"(bar_full + 8 * s), "r"(0), "r"(row), "h"((uint16_t)((1u << CL) - 1)), "l"(pol) : "memory");
                    }
                    if (HELPER) {
                        if (lane == 0) { sts32(tk + ((j & 7) << 2), valid ? (uint32_t)t : NO_TILE); mbar_expect_tx(bar_full + 8 * s, valid ? TILE_BYTES : 0); }
                    } else if (lane < CL) {
                        asm volatile("mbarrier.arrive.expect_tx.shared::cluster.b64 _, [%0], %1;" :: "r"(rfull + 8 * s), "r"(valid ? TILE_BYTES + 4 : 4) : "memory");
                        st_async(rtk + ((j & 7) << 2), valid ? (uint32_t)t : NO_TILE, rfull + 8 * s);
                    }
                    if (!valid) break;
                    if (!HELPER && lane == 0 && t > p.ta) {
                        auto fr = [&](int m) { const int f = m + p.leade + max(0, (p.slope1 * (p.te - m)) >> 16); return f < ntiles ? place<false>(p, f) : p.alltiles - p.nht; };
                        const int u1 = fr(t);
                        for (int u = fr(t - 1); u < u1; u++)
                            asm volatile("cp.async.bulk.prefetch.L2.global [%0], %1;" :: "l"(p.x + (size_t)u * TILE_BYTES), "r"(min(NT, p.ntok - u * NT) * (D * 2)) : "memory");
                    }
                    if (!HELPER && lane == 0 && j >= NSLOT - 1) drawn = atomicInc(&g_ticket, ntiles - p.ncl * (NSLOT - 1) - 1);
                    if (++s == NSLOT) { s = 0; ph ^= 1; }
                }
            }
        } else {
            const int g = warp - 13;
            const uint32_t rempty = HELPER ? bar_empty : mapa(bar_empty, 0);
            if (g == 0 && lane == 0) { sts32(sb + OFF_EPOCH + 8, epoch); mbar_arrive(sb + OFF_EPOCH); }
            mbar_wait(bar_full, 0);
            uint32_t t = lds32v(tk), ph = 0;
            int s = 0, nheld = 0, nout = 0, hnext = p.nh == 0 ? -1 : p.jh + cid % p.jm;
            const int nh = p.nh + (g == 0);
            uint32_t held[NH + 1];
            auto store = [&](int buf, uint32_t tile) {
                asm volatile("cp.async.bulk.tensor.2d.global.shared::cta.bulk_group.L2::cache_hint [%0, {%2, %3}], [%1], %4;"
                             :: "l"(&tmo), "r"(sb + OFF_STG + (buf * 3 + g) * STG_BYTES), "r"((g * 3 + rank) * 64), "r"((place<HELPER>(p, tile)) * NT), "l"(pol) : "memory");
            };
            auto release = [&]() {
#pragma unroll
                for (int k = 0; k <= NH; k++) if (k >= nout && k < nheld && lane == 0) store(1 + k, held[k]);
                nout = nheld;
            };
            for (int i = 0;; i++) {
                bar_sync(BAR_SFULL + g, 160);
                const int s1 = s + 1 == NSLOT ? 0 : s + 1;
                if (s1 == 0) ph ^= 1;
                if (lane == 0 && g < 2) { if (HELPER) mbar_arrive(bar_empty + 8 * s); else mbar_arrive_cluster(rempty + 8 * s); }
                const bool ready = __all_sync(~0u, mbar_test(bar_full + 8 * s1, ph));
                if (ready) bar_arrive(BAR_G + g, 288);
                if (lane == 0) {
                    asm volatile("fence.proxy.async.shared::cta;" ::: "memory");
                    if (i != hnext) store(0, t);
                    asm volatile("cp.async.bulk.commit_group;" ::: "memory");
                    if (g == 2 && i == 0 && atomicInc(&g_passed, p.nctas - 1) == (uint32_t)p.nctas - 1) atomicAdd(&g_epoch, 1);
                }
                __syncwarp();
                if (i == hnext) {
#pragma unroll
                    for (int k = 0; k <= NH; k++) if (k == nheld) held[k] = t;
                    hnext = ++nheld < nh ? hnext + p.jd : -1;
                }
                s = s1;
                if (!ready) { mbar_wait(bar_full + 8 * s, ph); bar_arrive(BAR_G + g, 288); }
                t = lds32v(tk + (((i + 1) & 7) << 2));
                if (t >= (uint32_t)p.rel && nout < nheld) { release(); if (lane == 0) asm volatile("cp.async.bulk.commit_group;" ::: "memory"); }
                if (lane == 0) asm volatile("cp.async.bulk.wait_group.read 0;" ::: "memory");
                __syncwarp();
                if (t == NO_TILE) break;
                bar_arrive(BAR_SEMPTY + g, 160);
            }
        }
        __syncwarp();
        if (!HELPER) asm volatile("barrier.cluster.arrive.relaxed.aligned;\nbarrier.cluster.wait.aligned;" ::: "memory");
    } else {
        asm volatile("setmaxnreg.inc.sync.aligned.u32 160;");
        const int wg = warp >> 2, r = lane >> 2, q = lane & 3;
        uint32_t epoch;
        if (HELPER) asm volatile("bar.sync 0;" ::: "memory");
        else {
            int prb = cid;
            asm volatile("barrier.cluster.arrive.relaxed.aligned;" ::: "memory");
            if (prb >= 36) asm volatile("barrier.cluster.wait.aligned;" ::: "memory");
#pragma unroll 1
            for (int round = 0; prb < 36; prb += p.ncl, round++) {
                const uint32_t wsm = sb + OFF_WST, msk = sb + OFF_MSK + (round & 1) * 144, mbar = sb + OFF_MBAR + (round & 1) * 8;
                if (round) {
                    bar_sync(3, 384);
                    if (tid == 0) mbar_expect_tx(mbar, 36 * 4);
                    prep_load(prb);
                }
                const uint32_t tk2 = min2(min2(tie_key(wv[0].x, wv[1].x, wv[2].x, wv[3].x), tie_key(wv[0].y, wv[1].y, wv[2].y, wv[3].y)),
                                          min2(tie_key(wv[0].z, wv[1].z, wv[2].z, wv[3].z), tie_key(wv[0].w, wv[1].w, wv[2].w, wv[3].w)));
                const uint32_t mk = __ballot_sync(~0u, (tk2 & 0xFFFFu) == 0 || tk2 < 0x10000u);
                if (round == 0) asm volatile("barrier.cluster.wait.aligned;" ::: "memory");
                if (lane < CL) st_async(mapa(msk + (rank * 12 + warp) * 4, lane), mk, mapa(mbar, lane));
#pragma unroll
                for (int j = 0; j < 4; j++) {
                    const int row = wrow + j;
                    const uint32_t ad = wsm + row * 128 + (((lane >> 2) ^ ((row & 1) | ((row >> 1) & 6))) << 4);
                    asm volatile("st.shared.v4.b32 [%0], {%1,%2,%3,%4};" :: "r"(ad), "r"(wv[j].x), "r"(wv[j].y), "r"(wv[j].z), "r"(wv[j].w) : "memory");
                }
                if (warp >= 6) bar_arrive(1, 384);
                else {
                    bar_sync(1, 384);
                    mbar_wait(sb + OFF_EPOCH, 0);
                    epoch = lds32v(sb + OFF_EPOCH + 8);
                    uint8_t* const scr = (uint8_t*)p.scr + (epoch & 1) * SCR_END;
                    mbar_wait(mbar, (round >> 1) & 1);
                    uint32_t m0 = 0, m1 = 0;
                    if (lane < KSTEPS) asm volatile("ld.volatile.shared.v2.b32 {%0,%1}, [%2];" : "=r"(m0), "=r"(m1) : "r"(msk + 8 * lane) : "memory");
                    uint32_t c0 = m0 - ((m0 >> 1) & 0x55555555u), c1 = m1 - ((m1 >> 1) & 0x55555555u);
                    c0 = (c0 & 0x33333333u) + ((c0 >> 2) & 0x33333333u) + (c1 & 0x33333333u) + ((c1 >> 2) & 0x33333333u);
                    c1 = __reduce_add_sync(~0u, (c0 >> 4) & 0x0F0F0F0Fu); c0 = __reduce_add_sync(~0u, c0 & 0x0F0F0F0Fu);
                    auto key = [&](int v) { return ((((v & 1) ? c1 : c0) >> (4 * (v & 6))) & 0xFFu) * 8 + v; };
                    const uint32_t ku = key(lane & 7);
                    const uint32_t l0 = __ballot_sync(~0u, key(lane >> 3) < ku), l1 = __ballot_sync(~0u, key(4 + (lane >> 3)) < ku);
                    const int rk = __popc((l0 >> (lane & 7)) & 0x01010101u) + __popc((l1 >> (lane & 7)) & 0x01010101u);
                    const int pp = prb & 3;
                    const int ulo = __ffs(__ballot_sync(~0u, rk == pp)) - 1, uhi = __ffs(__ballot_sync(~0u, rk == 7 - pp)) - 1;
                    uint32_t lo[4], hi[4];
                    load_unit(wsm, warp, ulo, lane, lo); load_unit(wsm, warp, uhi, lane, hi);
                    const uint32_t mm = (((m0 >> (4 * ulo)) | (m0 >> (4 * uhi))) & 15u) | ((((m1 >> (4 * ulo)) | (m1 >> (4 * uhi))) & 15u) << 4);
                    const uint2 bias2 = make_uint2(__shfl_sync(~0u, ulo < 4 ? b0 : b1, (ulo * 8 + r) & 31) * 0x10001u, __shfl_sync(~0u, uhi < 4 ? b0 : b1, (uhi * 8 + r) & 31) * 0x10001u);
                    emit_step(lo, hi, mm, prb, rank * 6 + warp, lane, ulo | (uhi << 4), bias2, scr, p.over, epoch + 1);
                }
            }
            if (cid >= 36 || warp >= 6) { mbar_wait(sb + OFF_EPOCH, 0); epoch = lds32v(sb + OFF_EPOCH + 8); }
            if (warp >= 6) for (int i = blockIdx.x * 192 + tid - 192; i < SCR_END / 16; i += gridDim.x * 192) p.scr[(~epoch & 1) * (SCR_END / 16) + i] = make_uint4(0, 0, 0, 0);
        }
        if (HELPER) { mbar_wait(sb + OFF_EPOCH, 0); epoch = lds32v(sb + OFF_EPOCH + 8); }
        if (wg == 2) bar_arrive(BAR_T, 256);
        const int mt = wg * 3 + rank, rb = mt * 4 + (warp & 3);
        const uint8_t* const scr = (const uint8_t*)p.scr + (epoch & 1) * SCR_END + mt * BLK;
        const int fo = (warp & 3) * 512 + lane * 16, io = BLK_I + (warp & 3) * 128 + r * 16, sl = (r >> 1) * 8 + q * 2 + (r & 1), so = BLK_S + (warp & 3) * 2560 + sl * 16;
        const int mo = BLK_M + ((warp & 3) * KSTEPS + (q >> 1)) * 64 + r * 8 + (q & 1) * 4;
        if (!HELPER && cid < 36) bar_sync(2, 384);
        const uint32_t blk = sb + blk_off(wg);
        if (warp == 0) {
            if (HELPER || cid >= 36 || p.ncl < 36) for (int n = 0; __any_sync(~0u, ld32(scr + 17 * 2048 + fo) == 0); n++) fail_if(n > (1 << 22));
            if (lane < 3) {
                mbar_expect_tx(sb + OFF_FB + 8 * lane, BLK);
                asm volatile("cp.async.bulk.shared::cluster.global.mbarrier::complete_tx::bytes [%0], [%1], %2, [%3];"
                             :: "r"(sb + blk_off(lane)), "l"(scr + lane * 3 * BLK), "r"(BLK), "r"(sb + OFF_FB + 8 * lane) : "memory");
            }
        }
        uint32_t a[KSTEPS][4], meta[9];
        uint2 rv[5]; uint32_t ro[5];
        uint32_t info, bias_lo, bias_hi;
        {
            const uint8_t* const fp = scr + fo; const uint8_t* const ip = scr + io; const uint8_t* const sp = scr + so; const uint8_t* const mp = scr + mo;
            mbar_wait(sb + OFF_FB + 8 * wg, 0);
            uint4 i0 = lds128(blk + io), sv[5];
#pragma unroll
            for (int j = 0; j < 5; j++) sv[j] = lds128(blk + so + j * 512);
#pragma unroll
            for (int j = 0; j < 9; j++) meta[j] = lds32(blk + mo + j * 128);
#pragma unroll
            for (int k = 0; k < KSTEPS; k++) { const uint4 v = lds128(blk + fo + k * 2048); a[k][0] = v.x; a[k][1] = v.y; a[k][2] = v.z; a[k][3] = v.w; }
            for (int n = 0;; n++) {
                uint32_t lo = __vimin3_u32(__vimin3_u32(i0.x, meta[8], sv[0].z), sv[1].z, __vimin3_u32(sv[2].z, sv[3].z, sv[4].z));
#pragma unroll
                for (int j = 0; j < 8; j += 2) lo = __vimin3_u32(lo, meta[j], meta[j + 1]);
#pragma unroll
                for (int k = 0; k < KSTEPS; k += 2) lo = __vimin3_u32(lo, a[k][0], a[k + 1][0]);
                if (__all_sync(~0u, lo != 0)) break;
                fail_if(n > (1 << 20));
                ld128_if(i0.x == 0, ip, i0.x, i0.y, i0.z, i0.w);
#pragma unroll
                for (int j = 0; j < 5; j++) ld128_if(sv[j].z == 0, sp + j * 512, sv[j].x, sv[j].y, sv[j].z, sv[j].w);
#pragma unroll
                for (int j = 0; j < 9; j++) ld32_if(meta[j] == 0, mp + j * 128, meta[j]);
#pragma unroll
                for (int k = 0; k < KSTEPS; k++) ld128_if(a[k][0] == 0, fp + k * 2048, a[k][0], a[k][1], a[k][2], a[k][3]);
            }
            info = i0.x; bias_lo = i0.y; bias_hi = i0.z;
#pragma unroll
            for (int j = 0; j < 5; j++) { rv[j] = make_uint2(sv[j].x, sv[j].y); ro[j] = sv[j].z; }
        }
#pragma unroll
        for (int j = 0; j < 4; j++) { rv[j].x ^= p.zero; rv[j].y ^= p.zero; }
        if ((wg || !BLK_FITS) && lane == 0) { if (HELPER) mbar_arrive(sb + OFF_GO + 8 * wg); else mbar_arrive_cluster(mapa(sb + OFF_GO + 8 * wg, 0)); }
        info = __shfl_sync(~0u, info, 0);
        const int ngrp = info & 0xFF, ulo = (info >> 8) & 7, uhi = (info >> 12) & 7;
#pragma unroll 1
        for (int j = 5; j < ngrp; j++)
            for (int n = 0; __any_sync(~0u, ld128(p.over + (rb * 36 + j) * 32 + sl).w != epoch + 1); n++) fail_if(n > (1 << 20));
        mbar_wait(bar_full, 0);
        const uint32_t stg = sb + OFF_STG + wg * STG_BYTES + ((lane >> 4) * 8 + (lane & 7)) * 128 + (((((lane >> 3) & 1) ? uhi : ulo) ^ (lane & 7)) << 4);
        float acc[NACC];
        uint32_t bq[NB][2], b4[NB];
        auto gather = [&](uint32_t xb) {
#pragma unroll
            for (int j = 0; j < 3; j++)
#pragma unroll
                for (int n = 0; n < NB; n++) { const uint32_t v = lds32(xb + ro[j] + (n * 9216 - RO_BIAS)); if (j < 2) acc[4 * n + j] = __uint_as_float(v); else bq[n][0] = v; }
            if (ngrp > 3) {
#pragma unroll
                for (int n = 0; n < NB; n++) bq[n][1] = lds32(xb + ro[3] + (n * 9216 - RO_BIAS));
                if (ngrp > 4) {
#pragma unroll
                    for (int n = 0; n < NB; n++) b4[n] = lds32(xb + ro[4] + (n * 9216 - RO_BIAS));
                }
            }
        };
        const int me = tid >> 7, nxt = __shfl_sync(~0u, BAR_T + (me == 2 ? 0 : me + 1), 0), prv = __shfl_sync(~0u, BAR_G + (me == 0 ? 2 : me - 1), 0);
#pragma unroll
        for (int n = 0; n < NB; n++) b4[n] = bq[n][1] = 0;
        gather(sb + OFF_X);
        bar_sync(BAR_T + wg, 256);
        auto bdesc = [](uint32_t x) { return ((uint64_t)1 << 62) | ((uint64_t)(9216 >> 4) << 32) | ((uint64_t)1 << 16) | (uint64_t)(x >> 4); };
        uint32_t xb = sb + OFF_X;
        uint64_t desc = bdesc(xb);
        const uint32_t re0 = HELPER ? bar_empty : mapa(bar_empty, 0);
        uint32_t re = re0;
        const bool releases = tid >= 256 && lane == 0;
        int hnext = p.nh == 0 ? -1 : p.jh + cid % p.jm, hbuf = 3 * STG_BYTES;
        bool more = true;
        for (int i = 0; more; i++) {
            auto rows03 = [&]() {
#pragma unroll
                for (int n = 0; n < NB; n++) mma_k16(acc + 4 * n, rv[0], rv[1], __float_as_uint(acc[4 * n]), __float_as_uint(acc[4 * n + 1]), 0.f, 0.f, 0.f, 0.f);
#pragma unroll
                for (int n = 0; n < NB; n++) mma_k16(acc + 4 * n, rv[2], rv[3], bq[n][0], bq[n][1], acc[4 * n], acc[4 * n + 1], acc[4 * n + 2], acc[4 * n + 3]);
            };
            if (ngrp <= 4) rows03();
            else {
                rows03();
#pragma unroll
                for (int n = 0; n < NB; n++) mma_k8(acc + 4 * n, rv[4], b4[n]);
#pragma unroll 1
                for (int j = 5; j < ngrp; j++) {
                    const uint4 o = __ldca(p.over + (rb * 36 + j) * 32 + sl);
#pragma unroll
                    for (int n = 0; n < NB; n++) b4[n] = lds32(xb + o.z + (n * 9216 - RO_BIAS));
#pragma unroll
                    for (int n = 0; n < NB; n++) mma_k8(acc + 4 * n, make_uint2(o.x, o.y), b4[n]);
                }
            }
            asm volatile("wgmma.fence.sync.aligned;" ::: "memory");
#pragma unroll
            for (int k = 0; k < KSTEPS; k++) {
                const uint64_t d = desc + (uint64_t)(((k >> 1) * 1024 + (k & 1) * 64) >> 4);
                if (k & 1) wgmma_sp<1>(acc, a[k], d, meta[k >> 1]);
                else       wgmma_sp<0>(acc, a[k], d, meta[k >> 1]);
                if (k == SPLIT - 1) asm volatile("wgmma.commit_group.sync.aligned;" ::: "memory");
            }
            asm volatile("wgmma.commit_group.sync.aligned;" ::: "memory");
            bar_arrive(nxt, 256);
            xb = xb == sb + OFF_X + (NSLOT - 1) * TILE_BYTES ? sb + OFF_X : xb + TILE_BYTES;
            desc = bdesc(xb);
            uint32_t sq = stg;
            if (i == hnext) { sq += hbuf; hbuf += 3 * STG_BYTES; hnext = hbuf <= (p.nh + (wg == 0)) * 3 * STG_BYTES ? hnext + p.jd : -1; }
            asm volatile("wgmma.wait_group.sync.aligned 1;" ::: "memory");
            if (wg != 0 || i != 0) bar_arrive(prv, 288);
            if (i != 0) bar_sync(BAR_SEMPTY + me, 160);
            asm volatile("wgmma.wait_group.sync.aligned 0;" ::: "memory");
            if (releases) { if (HELPER) mbar_arrive(re); else mbar_arrive_cluster(re); }
            re = re == re0 + 8 * (NSLOT - 1) ? re0 : re + 8;
#pragma unroll
            for (int n = 0; n + 1 < NB; n += 2) {
                const uint32_t p0 = pack_bias(acc[4 * n], acc[4 * n + 1], bias_lo), p1 = pack_bias(acc[4 * n + 2], acc[4 * n + 3], bias_hi);
                const uint32_t p2 = pack_bias(acc[4 * n + 4], acc[4 * n + 5], bias_lo), p3 = pack_bias(acc[4 * n + 6], acc[4 * n + 7], bias_hi);
                asm volatile("stmatrix.sync.aligned.m8n8.x4.trans.shared.b16 [%0], {%1,%2,%3,%4};" :: "r"(sq + n * 1024), "r"(p0), "r"(p1), "r"(p2), "r"(p3) : "memory");
            }
            if (NB & 1) {
                const uint32_t p0 = pack_bias(acc[NACC - 4], acc[NACC - 3], bias_lo), p1 = pack_bias(acc[NACC - 2], acc[NACC - 1], bias_hi);
                asm volatile("stmatrix.sync.aligned.m8n8.x2.trans.shared.b16 [%0], {%1,%2};" :: "r"(sq + (NB - 1) * 1024), "r"(p0), "r"(p1) : "memory");
            }
            bar_arrive(BAR_SFULL + me, 160);
            bar_sync(BAR_G + me, 288);
            const uint32_t tn = lds32v(tk + (((i + 1) & 7) << 2));
            gather(xb);
            more = __any_sync(~0u, tn != NO_TILE);
            if (more || wg == 0) bar_sync(BAR_T + me, 256);
        }
        if (wg == 0) bar_arrive(BAR_G + 2, 288);
        __syncwarp();
        if (!HELPER) asm volatile("barrier.cluster.arrive.relaxed.aligned;\nbarrier.cluster.wait.aligned;" ::: "memory");
    }
}

typedef CUresult (*EncodeFn)(CUtensorMap*, CUtensorMapDataType, cuuint32_t, void*, const cuuint64_t*, const cuuint64_t*, const cuuint32_t*, const cuuint32_t*,
                             CUtensorMapInterleave, CUtensorMapSwizzle, CUtensorMapL2promotion, CUtensorMapFloatOOBfill);

extern "C" void kernel_launch(void* const* d_in, const int* in_sizes, int n_in, void* d_out, int out_size) {
    static EncodeFn enc = nullptr;
    static int ncl = 0, nhelp = 0;
    const int ntok = in_sizes[0] / D;
    cudaLaunchConfig_t cfg = {};
    cudaLaunchAttribute at[1];
    at[0].id = cudaLaunchAttributeClusterDimension; at[0].val.clusterDim.x = CL; at[0].val.clusterDim.y = 1; at[0].val.clusterDim.z = 1;
    cfg.blockDim = dim3(NTHREADS); cfg.dynamicSmemBytes = SMEM_BYTES; cfg.attrs = at; cfg.numAttrs = 1; cfg.stream = cudaStreamPerThread;
    if (!enc) {
        cudaDriverEntryPointQueryResult qr; void* fn = nullptr;
        cudaGetDriverEntryPoint("cuTensorMapEncodeTiled", &fn, cudaEnableDefault, &qr);
        enc = (EncodeFn)fn;
        cudaFuncSetAttribute(spgemm_kernel<false>, cudaFuncAttributeMaxDynamicSharedMemorySize, SMEM_BYTES);
        cudaFuncSetAttribute(spgemm_kernel<true>, cudaFuncAttributeMaxDynamicSharedMemorySize, SMEM_BYTES);
        int dev = 0, nsm = 0;
        cudaGetDevice(&dev);
        cudaDeviceGetAttribute(&nsm, cudaDevAttrMultiProcessorCount, dev);
        cfg.gridDim = dim3(CL * (nsm / CL));
        cudaOccupancyMaxActiveClusters(&ncl, spgemm_kernel<false>, &cfg);
        if (ncl < 1) ncl = 1;
        nhelp = nsm > CL * ncl ? (nsm - CL * ncl) / CL : 0;
    }
    CUtensorMap tmx, tmo;
    {
        cuuint64_t dims[4] = {64, 8, 9, (cuuint64_t)(ntok / 8)};
        cuuint64_t strides[3] = {D * 2, 128, 8 * D * 2};
        cuuint32_t box[4] = {64, 8, 9, NB}, es[4] = {1, 1, 1, 1};
        enc(&tmx, CU_TENSOR_MAP_DATA_TYPE_BFLOAT16, 4, d_in[0], dims, strides, box, es, CU_TENSOR_MAP_INTERLEAVE_NONE,
            CU_TENSOR_MAP_SWIZZLE_128B, CU_TENSOR_MAP_L2_PROMOTION_L2_128B, CU_TENSOR_MAP_FLOAT_OOB_FILL_NONE);
    }
    {
        cuuint64_t dims[2] = {D, (cuuint64_t)ntok};
        cuuint64_t strides[1] = {D * 2};
        cuuint32_t box[2] = {64, NT}, es[2] = {1, 1};
        enc(&tmo, CU_TENSOR_MAP_DATA_TYPE_BFLOAT16, 2, d_out, dims, strides, box, es, CU_TENSOR_MAP_INTERLEAVE_NONE,
            CU_TENSOR_MAP_SWIZZLE_128B, CU_TENSOR_MAP_L2_PROMOTION_NONE, CU_TENSOR_MAP_FLOAT_OOB_FILL_NONE);
    }
    Params p;
    p.w = (const uint16_t*)d_in[1]; p.bias = (const uint16_t*)d_in[2]; p.x = (const uint8_t*)d_in[0];
    p.ntok = ntok;
    cudaGetSymbolAddress((void**)&p.scr, g_scr); cudaGetSymbolAddress((void**)&p.over, g_over);
    p.zero = 0;
    p.alltiles = (ntok + NT - 1) / NT;
    const int nc = ncl < p.alltiles ? ncl : p.alltiles;
    p.a = nhelp ? (int)(2 * nc / (nhelp * 1.0) + 0.5) : 2;
    if (p.a < 2) p.a = 2;
    const int nblk = (int)(p.alltiles / (p.a + 2) * 0.7);
    const int nh = nhelp && 2 * nblk >= nhelp && p.alltiles - 2 * nblk >= nc ? nhelp : 0;
    p.nha = nh ? 2 * nblk : 0; p.nht = p.alltiles > 16 * nc ? nh : 0;
    p.ntiles = p.alltiles - p.nha - p.nht;
    p.trig = p.ntiles - nc * NSLOT - 30;
    p.nfull = nh ? nblk * p.a : 0; p.amagic = (int)(0xFFFFFFFFu / (uint32_t)p.a + 1);
    p.ncl = nc; p.nctas = CL * (nc + nh);
    p.nh = (int)NH; p.jh = 2; p.jm = 4; p.jd = 5; p.rel = p.ntiles - 50;
    auto tiles = [](double v) { return (int)(v * 56 / NT); };
    auto ns = [](double v) { return (int)(v * NT / 56); };
    p.pfd = 1500; p.pk = ns(600);
    p.ta = (int)(p.ntiles * 0.33) + 1; p.lead1 = tiles(280); p.pw = 2750;
    p.k1 = tiles(68); p.pfs = ns(700); p.pfs2 = ns(1950);
    p.te = p.ntiles + 2; p.leade = tiles(45); p.slope1 = ((p.lead1 - p.leade) << 16) / (p.te - p.ta);
    cfg.gridDim = dim3(CL * nc);
    cudaLaunchKernelEx(&cfg, spgemm_kernel<false>, tmx, tmo, p);
    if (nh) {
        at[0].id = cudaLaunchAttributeProgrammaticStreamSerialization; at[0].val.programmaticStreamSerializationAllowed = 1;
        cfg.gridDim = dim3(CL * nh);
        p.ncl = nh;
        p.nh = p.nht ? NH : 0; p.jh = p.nha / nh - 10; p.jd = 1; p.jm = 1; p.rel = p.nha;
        cudaLaunchKernelEx(&cfg, spgemm_kernel<true>, tmx, tmo, p);
    }
}
```
